```python
import torch

def _softmax(x, axis=-1):
    return torch.softmax(x, dim=axis)
def _gelu(x):
    return torch.nn.functional.gelu(x, approximate="tanh")
def _silu(x):
    return torch.nn.functional.silu(x)
def _sigmoid(x):
    return torch.sigmoid(x)
def _layernorm(x, axis=-1, eps=1e-5):
    m = x.mean(dim=axis, keepdim=True)
    v = x.var(dim=axis, keepdim=True, unbiased=False)
    return (x - m) / torch.sqrt(v + eps)
def _scatter_add(tgt, idx, src, axis=0):
    return tgt.clone().index_add_(axis, idx, src)
def _segment_sum(src, seg, n):
    out = torch.zeros((n,) + src.shape[1:], dtype=src.dtype)
    return out.index_add_(0, seg, src)
def _pad(x, pw):
    flat = tuple(v for pair in reversed(pw) for v in pair)
    return torch.nn.functional.pad(x, flat)

kernel_name = 'recurrent_scan__spectral_fnet__moe_arch_mod__prompt'

def setup_inputs():

    _w = (lambda a: (lambda t: t.to(torch.bfloat16) if t.is_floating_point() else t)(torch.as_tensor(a)))
    def _A_setup():
        B, S, D = 1, 2048, 1024
        ns = torch.arange(S)[:, None] * torch.arange(S)[None, :]
        nd = torch.arange(D)[:, None] * torch.arange(D)[None, :]
        Ws_re = torch.cos(-2.0 * torch.pi * ns / S).to(float)
        Ws_im = torch.sin(-2.0 * torch.pi * ns / S).to(float)
        Wd_re = torch.cos(-2.0 * torch.pi * nd / D).to(float)
        Wd_im = torch.sin(-2.0 * torch.pi * nd / D).to(float)
        return {
            "x": _w((lambda *s: torch.randn(*s, dtype=torch.bfloat16) * 0.05)(B, S, D)),
            "dft_seq_re": _w(Ws_re),
            "dft_seq_im": _w(Ws_im),
            "dft_hid_re": _w(Wd_re),
            "dft_hid_im": _w(Wd_im),
        }
    _A_in = _A_setup()

    def _B_setup():
        B, S, D, F, C = 1, 2048, 1024, 3584, 1
        return {
            "x": _w((lambda *s: torch.randn(*s, dtype=torch.bfloat16) * 0.05)(B, S, D)),
            "w_r": _w((lambda *s: torch.randn(*s, dtype=torch.bfloat16) * 0.05)(D)),
            "w_gate": _w((lambda *s: torch.randn(*s, dtype=torch.bfloat16) * 0.05)(D, F)),
            "w_up": _w((lambda *s: torch.randn(*s, dtype=torch.bfloat16) * 0.05)(D, F)),
            "w_down": _w((lambda *s: torch.randn(*s, dtype=torch.bfloat16) * 0.05)(F, D)),
        }
    _B_in = _B_setup()

    return {
        "A_x": _A_in["x"],
        "A_dft_seq_re": _A_in["dft_seq_re"],
        "A_dft_seq_im": _A_in["dft_seq_im"],
        "A_dft_hid_re": _A_in["dft_hid_re"],
        "A_dft_hid_im": _A_in["dft_hid_im"],
        "B_x": _B_in["x"],
        "B_w_r": _B_in["w_r"],
        "B_w_gate": _B_in["w_gate"],
        "B_w_up": _B_in["w_up"],
        "B_w_down": _B_in["w_down"],
    }

def reference(A_x, A_dft_seq_re, A_dft_seq_im, A_dft_hid_re, A_dft_hid_im, B_x, B_w_r, B_w_gate, B_w_up, B_w_down):
    def _A_ref(x, dft_seq_re, dft_seq_im, dft_hid_re, dft_hid_im):
        a = torch.einsum("bsd,ed->bse", x, dft_hid_re)
        b = torch.einsum("bsd,ed->bse", x, dft_hid_im)
        y = torch.einsum("ts,bse->bte", dft_seq_re, a) - torch.einsum("ts,bse->bte", dft_seq_im, b)
        return y

    def _B_ref(x, w_r, w_gate, w_up, w_down):
        B, S, D = x.shape
        C = 1
        r = x @ w_r
        idx = torch.argsort(-r, axis=-1)[:, :C]
        idx_e = (lambda x, n, axis: torch.repeat_interleave(x, n, dim=axis))(idx.reshape(B, C, 1), D, axis=2)
        x_sel = (lambda x, i, axis: torch.take_along_dim(x, i, dim=axis))(x, idx_e, axis=1)
        g = _silu(x_sel @ w_gate)
        u = x_sel @ w_up
        y = (g * u) @ w_down
        r_sel = _sigmoid((lambda x, i, axis: torch.take_along_dim(x, i, dim=axis))(r, idx, axis=1))
        y = y * r_sel.reshape(B, C, 1)
        b_off = (torch.arange(B) * S).reshape(B, 1)
        flat_idx = (idx + b_off).reshape(B * C)
        zero = (x * 0.0).reshape(B * S, D)
        upd = _scatter_add(zero, flat_idx, y.reshape(B * C, D), axis=0)
        return x + upd.reshape(B, S, D)

    x = A_x
    xn = _layernorm(x, axis=-1)
    s = _A_ref(xn, A_dft_seq_re, A_dft_seq_im, A_dft_hid_re, A_dft_hid_im)
    g = _silu(_B_ref(xn, B_w_r, B_w_gate, B_w_up, B_w_down))
    return x + s * g
```

```cpp
#include <cuda_runtime.h>
#include <cuda_bf16.h>
#include <cuda.h>
#include <stdint.h>

#define PACE1 450
#define PACE2 1400
#define PACE3 2300
#define D0 4000
#define DGAP 800
#define DLAG 2
#define XPD 500
#define XPT 8400
#define BPT 12000
#define RSD 11000
#define GUS 29
#define CPN 4
#define GR 7
#define I0 0
#define SPW 5
#define SPG 700
#define DELAY0 2000
#define DELAY2 6000
#define SPACE0 1000
#define FRS 49
#define WS0 22
#define WS1 31
#define WS2 (42 - RS)
#define WS3 (45 - RS)
#define MSL 200
#define GATE_O 4
#define SNDN 7
#define SND0 0x7654321
#define SND1 0x7654321
#define STG 5
#define PRB 5
#define RCV 4
#define PRB1 PRB
#define RCV1 RCV
#define FRSH 3
#define HORD 0
#define HORD_OLD 0
#define SLEEP_NS 80
#define GOD 900
#define WSL 40
#define ALN_ST 1
#define ALN_CP 1
#define NOXCH 0

#define REMAP 20
#define RS 7
#define PROD_REGS 32
#define HELP_REGS 64
#define CONS_REGS 208
#define NB 8

namespace {

constexpr int S_ = 2048, D_ = 1024, F_ = 3584;
constexpr int NCTA = 128;
constexpr int OWN = GR * 128, SLR = (D_ - OWN) / 4;
constexpr int NMOE = 112;
constexpr uint32_t A_BYTES = 16384, B_BYTES = 32768, STAGE_BYTES = A_BYTES + B_BYTES;
constexpr uint32_t OFF_X = 4 * STAGE_BYTES;
constexpr uint32_t OFF_MO = OFF_X + 24576;
constexpr uint32_t OFF_SP = STAGE_BYTES + A_BYTES;
constexpr uint32_t OFF_BAR = OFF_X + 32768;
constexpr uint32_t OFF_XN = OFF_BAR + 304;
constexpr uint32_t OFF_RED = OFF_XN + 2112;
constexpr uint32_t OFF_H = OFF_RED + 512;
constexpr uint32_t OFF_SEL = OFF_H + 128;
constexpr uint32_t OFF_ALN = OFF_XN + 2096;
constexpr uint32_t SMEM_BYTES = OFF_SEL + 16;
constexpr uint32_t SB0 = 1024;
constexpr int NTHREADS = 512;
static_assert(SMEM_BYTES <= 232448, "smem");
__host__ __device__ constexpr uint32_t b2_off(int s) { return s == 1 ? OFF_X : (s == 0 ? 3 : s == 2 ? 0 : 2) * STAGE_BYTES + A_BYTES; }
__host__ __device__ constexpr int hs(int i) { return (i + 4 - RS) & 3; }
__host__ __device__ constexpr int hp(int i) { return ((48 - RS + i) >> 2) & 1; }
constexpr int NH = 2 * RS;
constexpr int DEADH = NH - 7;
__host__ __device__ constexpr uint32_t ha_off(int h) {
    return h % 7 == 0 ? OFF_SP : h % 7 == 1 ? OFF_SP + 16384 : h % 7 == 6 ? b2_off(hs(3)) + 16384 : hs(h % 7 - 2) * STAGE_BYTES;
}
__host__ __device__ constexpr uint32_t hb_off(int h) { return b2_off(hs((h % 7) >> 1)) + (h % 7 & 1) * 16384; }

enum {
    B_FULL = 0, B_EMPTY = 4,
    B_EPI = 8,
    B_HRD = 12,
    B_DR = 17,
    B_RSD = 21,
    B_STATS,
    B_W1M, B_W0D,
    B_HS,
    B_SPF,
    B_HX,
    B_SEL = B_HX + 3, B_GU, B_PEER, B_PR2, B_FIN, B_UPD,
    B_COUNT
};
__host__ __device__ constexpr int hf_bar(int h) { return h % 7 == 1 ? B_HX : h % 7 == 3 ? B_HX + 1 : h % 7 == 6 ? B_HX + 2 : B_FULL + hs(h % 7 == 5 ? 3 : (h % 7) >> 1); }
__host__ __device__ constexpr int hf_par(int h) { return (h % 7 == 1 || h % 7 == 3 || h % 7 == 6 ? 0 : hp(h % 7 == 5 ? 3 : (h % 7) >> 1)) ^ (h / 7); }
__host__ __device__ constexpr int he_bar(int h) { return h < 2 ? B_EMPTY + hs(h) : h < 6 ? B_EPI + h - 2 : B_EMPTY + hs(h - 4); }
__host__ __device__ constexpr int he_par(int h) { return h < 2 ? hp(h) : h < 6 ? 1 : hp(h - 4); }
constexpr uint32_t OFF_PARK = ha_off(DEADH);
constexpr uint32_t OFF_SROW = OFF_PARK + 6144;
__host__ __device__ constexpr uint32_t bar_count(int i) {
    return i < B_EMPTY ? 1 : i < B_HRD || i == B_W1M ? 4 : i < B_DR ? 12 : i <= B_RSD || i == B_SPF ? 3 : i == B_STATS ? 5 : 1;
}
constexpr uint32_t OFF_MIR = OFF_BAR + 288;
static_assert(8 * B_COUNT <= 288 && OFF_MIR + 16 <= OFF_XN, "barriers");

struct Scratch {
    uint4 part[2 * (NMOE / 2) * (D_ / 4)];
    uint4 xp[4 * S_];
    uint2 rs[2 * D_];
    uint4 best[2 * NCTA];
    uint4 gu[4 * F_];
    unsigned long long abflag[8 * 16];
    unsigned epoch[NCTA];
    alignas(128) unsigned aln[32 * 32];
    uint4 epoch2[4];
    alignas(1024) uint4 xch[NCTA * 2048];
    uint8_t ab[8u * 32u * 32768u];
};
__device__ __align__(1024) Scratch g_scr;
#define TRACE(i) do {} while (0)
#define TRACE_C(i) do {} while (0)
#define TRACE_G(i) do {} while (0)

__device__ __forceinline__ uint32_t smem_u32(const void* p) { return (uint32_t)__cvta_generic_to_shared(p); }
__device__ __forceinline__ void mbar_init(uint32_t bar, uint32_t cnt) {
    asm volatile("mbarrier.init.shared::cta.b64 [%0], %1;" ::"r"(bar), "r"(cnt) : "memory");
}
__device__ __forceinline__ unsigned clk_hi() { unsigned t; asm volatile("mov.u32 %0, %%clock_hi;" : "=r"(t)); return t; }
#define MBAR_WAIT_(name, sem, idle) \
__device__ __forceinline__ void name(uint32_t bar, uint32_t parity, unsigned dl) { \
    asm volatile("{\n.reg .pred p;\n.reg .b32 t;\nL:\nmbarrier.try_wait.parity" sem ".shared::cta.b64 p, [%0], %1;\n@p bra D;\n" idle \
                 "mov.u32 t, %%clock_hi;\nsetp.le.u32 p, t, %2;\n@p bra L;\nD:\n}" ::"r"(bar), "r"(parity), "r"(dl), "n"(SLEEP_NS) : "memory"); }
MBAR_WAIT_(mbar_wait_, "", "")
MBAR_WAIT_(mbar_wait_sleep_, "", "nanosleep.u32 %3;\n")
MBAR_WAIT_(mbar_wait_cluster_, ".acquire.cluster", "")
#define mbar_wait(bar, parity) mbar_wait_(bar, parity, dl)
#define mbar_wait_sleep(bar, parity) mbar_wait_sleep_(bar, parity, dl)
#define mbar_wait_cluster(bar, parity) mbar_wait_cluster_(bar, parity, dl)
#define IN_TIME() (clk_hi() <= dl)
__device__ __forceinline__ void st_async2(uint32_t dst, float a, float b, uint32_t bar) {
    asm volatile("st.async.weak.shared::cluster.mbarrier::complete_tx::bytes.v2.f32 [%0], {%1, %2}, [%3];" ::"r"(dst), "f"(a), "f"(b), "r"(bar) : "memory");
}
__device__ __forceinline__ void st_async4(uint32_t dst, float a, float b, float c, float d, uint32_t bar) {
    asm volatile("st.async.weak.shared::cluster.mbarrier::complete_tx::bytes.v4.f32 [%0], {%1, %2, %3, %4}, [%5];"
                 ::"r"(dst), "f"(a), "f"(b), "f"(c), "f"(d), "r"(bar) : "memory");
}
__device__ __forceinline__ void mbar_arrive(uint32_t bar) {
    asm volatile("mbarrier.arrive.shared::cta.b64 _, [%0];" ::"r"(bar) : "memory");
}
__device__ __forceinline__ void mbar_arrive_after(uint32_t bar, uint32_t data) { mbar_arrive(bar + (data & blockIdx.y)); }
__device__ __forceinline__ void mbar_arrive_cluster(uint32_t cluster_bar) {
    asm volatile("mbarrier.arrive.shared::cluster.b64 _, [%0];" ::"r"(cluster_bar) : "memory");
}
__device__ __forceinline__ void mbar_expect_tx(uint32_t bar, uint32_t bytes) {
    asm volatile("mbarrier.arrive.expect_tx.shared::cta.b64 _, [%0], %1;" ::"r"(bar), "r"(bytes) : "memory");
}
__device__ __forceinline__ bool elect_one() {
    uint32_t p;
    asm volatile("{\n.reg .pred p;\nelect.sync _|p, 0xffffffff;\nselp.u32 %0, 1, 0, p;\n}" : "=r"(p));
    return p;
}
__device__ __forceinline__ uint32_t mapa(uint32_t addr, uint32_t rank) {
    uint32_t r;
    asm("mapa.shared::cluster.u32 %0, %1, %2;" : "=r"(r) : "r"(addr), "r"(rank));
    return r;
}
__device__ __forceinline__ void tma_2d(uint32_t dst, const CUtensorMap* tm, int c0, int c1, uint32_t bar) {
    asm volatile("cp.async.bulk.tensor.2d.shared::cluster.global.mbarrier::complete_tx::bytes [%0], [%1, {%3, %4}], [%2];"
                 ::"r"(dst), "l"(tm), "r"(bar), "r"(c0), "r"(c1) : "memory");
}
__device__ __forceinline__ void tma_2d_mc(uint32_t dst, const CUtensorMap* tm, int c0, int c1, uint32_t bar) {
    asm volatile("cp.async.bulk.tensor.2d.shared::cluster.global.mbarrier::complete_tx::bytes.multicast::cluster [%0], [%1, {%3, %4}], [%2], %5;"
                 ::"r"(dst), "l"(tm), "r"(bar), "r"(c0), "r"(c1), "h"((uint16_t)3) : "memory");
}
__device__ __forceinline__ void bulk_g2s_mc(uint32_t dst, const void* src, uint32_t bytes, uint32_t bar) {
    asm volatile("cp.async.bulk.shared::cluster.global.mbarrier::complete_tx::bytes.multicast::cluster [%0], [%1], %2, [%3], %4;"
                 ::"r"(dst), "l"(src), "r"(bytes), "r"(bar), "h"((uint16_t)3) : "memory");
}
__device__ __forceinline__ void bulk_g2s(uint32_t dst, const void* src, uint32_t bytes, uint32_t bar) {
    asm volatile("cp.async.bulk.shared::cluster.global.mbarrier::complete_tx::bytes [%0], [%1], %2, [%3];"
                 ::"r"(dst), "l"(src), "r"(bytes), "r"(bar) : "memory");
}
__device__ __forceinline__ void fence_async_smem() { asm volatile("fence.proxy.async.shared::cta;" ::: "memory"); }
__device__ __forceinline__ void prefetch_tmap(const CUtensorMap* tm) {
    asm volatile("prefetch.tensormap [%0];" ::"l"(tm) : "memory");
}
__device__ __forceinline__ unsigned long long ld_relaxed64(const unsigned long long* p) {
    unsigned long long v; asm volatile("ld.relaxed.gpu.global.u64 %0, [%1];" : "=l"(v) : "l"(p) : "memory"); return v;
}
__device__ __forceinline__ unsigned ld_relaxed8(const uint8_t* p) {
    unsigned v; asm volatile("ld.relaxed.gpu.global.u8 %0, [%1];" : "=r"(v) : "l"(p) : "memory"); return v;
}
__device__ __forceinline__ unsigned load_epoch(const unsigned* p) {
    unsigned v; asm volatile("ld.global.u32 %0, [%1];" : "=r"(v) : "l"(p) : "memory"); return v + 1;
}
__device__ __forceinline__ unsigned ld_relaxed(const unsigned* p) {
    unsigned v; asm volatile("ld.relaxed.gpu.global.u32 %0, [%1];" : "=r"(v) : "l"(p) : "memory"); return v;
}
__device__ __forceinline__ uint4 ld_relaxed128(const uint4* p) {
    uint4 v;
    asm volatile("{\n.reg .b128 t;\n.reg .b64 lo, hi;\nld.relaxed.gpu.global.b128 t, [%4];\nmov.b128 {lo, hi}, t;\n"
                 "mov.b64 {%0, %1}, lo;\nmov.b64 {%2, %3}, hi;\n}"
                 : "=r"(v.x), "=r"(v.y), "=r"(v.z), "=r"(v.w) : "l"(p) : "memory");
    return v;
}
__device__ __forceinline__ void st_relaxed128(uint4* p, const uint4& v) {
    asm volatile("{\n.reg .b128 t;\n.reg .b64 lo, hi;\nmov.b64 lo, {%1, %2};\nmov.b64 hi, {%3, %4};\nmov.b128 t, {lo, hi};\n"
                 "st.relaxed.gpu.global.b128 [%0], t;\n}"
                 ::"l"(p), "r"(v.x), "r"(v.y), "r"(v.z), "r"(v.w) : "memory");
}
__device__ __forceinline__ __uint128_t make128(uint32_t a, uint32_t b, uint32_t c, uint32_t d) {
    __uint128_t v;
    asm volatile("{\n.reg .b64 lo, hi;\nmov.b64 lo, {%1, %2};\nmov.b64 hi, {%3, %4};\nmov.b128 %0, {lo, hi};\n}" : "=q"(v) : "r"(a), "r"(b), "r"(c), "r"(d));
    return v;
}
__device__ __forceinline__ void st_relaxed128(uint4* p, __uint128_t v) {
    asm volatile("st.relaxed.gpu.global.b128 [%0], %1;" ::"l"(p), "q"(v) : "memory");
}
__device__ __forceinline__ void st_relaxed64(uint2* p, uint32_t lo, uint32_t hi) {
    asm volatile("{\n.reg .b64 t;\nmov.b64 t, {%1, %2};\nst.relaxed.gpu.global.b64 [%0], t;\n}" ::"l"(p), "r"(lo), "r"(hi) : "memory");
}
__device__ __forceinline__ void stg128(void* p, uint32_t a, uint32_t b, uint32_t c, uint32_t d) {
    asm volatile("st.global.v4.u32 [%0], {%1,%2,%3,%4};" ::"l"(p), "r"(a), "r"(b), "r"(c), "r"(d) : "memory");
}
__device__ __forceinline__ void sts128(uint32_t p, uint32_t a, uint32_t b, uint32_t c, uint32_t d) {
    asm volatile("st.shared.v4.u32 [%0], {%1,%2,%3,%4};" ::"r"(p), "r"(a), "r"(b), "r"(c), "r"(d) : "memory");
}
__device__ __forceinline__ uint4 lds128(uint32_t p) {
    uint4 v;
    asm volatile("ld.shared.v4.u32 {%0,%1,%2,%3}, [%4];" : "=r"(v.x), "=r"(v.y), "=r"(v.z), "=r"(v.w) : "r"(p) : "memory");
    return v;
}
__device__ __forceinline__ void prefetch_l2(const void* p) { asm volatile("prefetch.global.L2 [%0];" ::"l"(p)); }
__device__ __forceinline__ void st_release8(void* p, unsigned v) {
    asm volatile("st.release.gpu.global.u8 [%0], %1;" ::"l"(p), "r"(v) : "memory");
}
__device__ __forceinline__ uint64_t policy_evict_first() {
    uint64_t pol;
    asm("createpolicy.fractional.L2::evict_first.b64 %0, 1.0;" : "=l"(pol));
    return pol;
}
__device__ __forceinline__ uint4 ldg_stream(const void* p, uint64_t pol) {
    uint4 v;
    asm volatile("ld.global.nc.L1::no_allocate.L2::cache_hint.v4.u32 {%0,%1,%2,%3}, [%4], %5;"
                 : "=r"(v.x), "=r"(v.y), "=r"(v.z), "=r"(v.w) : "l"(p), "l"(pol));
    return v;
}
__device__ __forceinline__ void ldg_stream_next(uint4& v, const char*& p, uint32_t stride, uint64_t pol) {
    asm volatile("{\n.reg .pred q;\nsetp.ne.u32 q, %5, 0;\n"
                 "@q ld.global.nc.L1::no_allocate.L2::cache_hint.v4.u32 {%0,%1,%2,%3}, [%4], %6;\nmad.wide.u32 %4, %5, 1, %4;\n}"
                 : "+r"(v.x), "+r"(v.y), "+r"(v.z), "+r"(v.w), "+l"(p) : "r"(stride), "l"(pol));
}
template <int ID, int N> __device__ __forceinline__ void named_arrive() { asm volatile("bar.arrive %0, %1;" ::"n"(ID), "n"(N) : "memory"); }
template <int ID, int N> __device__ __forceinline__ void named_bar() { asm volatile("bar.sync %0, %1;" ::"n"(ID), "n"(N) : "memory"); }

__device__ __forceinline__ float bf_lo(uint32_t u) { return __uint_as_float(u << 16); }
__device__ __forceinline__ float bf_hi(uint32_t u) { return __uint_as_float(u & 0xffff0000u); }
__device__ __forceinline__ uint32_t pack_bf(float lo, float hi) {
    uint32_t r; asm("cvt.rn.bf16x2.f32 %0, %1, %2;" : "=r"(r) : "f"(hi), "f"(lo)); return r;
}
__device__ __forceinline__ float rbf(float v) { return __uint_as_float(pack_bf(0.f, v)); }
__device__ __forceinline__ float silu_f(float z) { return __fdividef(z, 1.0f + __expf(-z)); }
__device__ __forceinline__ uint32_t bfma2(uint32_t a, uint32_t b, uint32_t c) {
    uint32_t r; asm("fma.rn.bf16x2 %0, %1, %2, %3;" : "=r"(r) : "r"(a), "r"(b), "r"(c)); return r;
}
__device__ __forceinline__ uint32_t norm2(uint32_t xv, float m, float rinv) {
    uint32_t t = pack_bf(bf_lo(xv) - m, bf_hi(xv) - m);
    return pack_bf(bf_lo(t) * rinv, bf_hi(t) * rinv);
}
__device__ __forceinline__ float gate1(float x, float rinv, float mr) {
    const float h = fmaf(x, 0.5f * rinv, 0.5f * mr);
    float t;
    asm("tanh.approx.f32 %0, %1;" : "=f"(t) : "f"(h));
    return fmaf(h, t, h);
}
__device__ __forceinline__ uint32_t gate2(uint32_t xv, float rinv, float mr) {
    return pack_bf(gate1(bf_lo(xv), rinv, mr), gate1(bf_hi(xv), rinv, mr));
}
__device__ __forceinline__ uint32_t silu2(uint32_t z) { return pack_bf(silu_f(bf_lo(z)), silu_f(bf_hi(z))); }

__device__ __forceinline__ void wg_fence() { asm volatile("wgmma.fence.sync.aligned;" ::: "memory"); }
__device__ __forceinline__ void wg_commit() { asm volatile("wgmma.commit_group.sync.aligned;" ::: "memory"); }
template <int N> __device__ __forceinline__ void wg_wait() { asm volatile("wgmma.wait_group.sync.aligned %0;" ::"n"(N) : "memory"); }

__host__ __device__ constexpr uint32_t desc_lo(uint32_t addr, uint32_t lbo) { return ((addr & 0x3FFFF) >> 4) | ((lbo >> 4) << 16); }

#define R8(a, o) "+f"(a[(o) + 0]), "+f"(a[(o) + 1]), "+f"(a[(o) + 2]), "+f"(a[(o) + 3]), \
                 "+f"(a[(o) + 4]), "+f"(a[(o) + 5]), "+f"(a[(o) + 6]), "+f"(a[(o) + 7])
#define R64(a, o) R8(a, (o) + 0), R8(a, (o) + 8), R8(a, (o) + 16), R8(a, (o) + 24), \
                  R8(a, (o) + 32), R8(a, (o) + 40), R8(a, (o) + 48), R8(a, (o) + 56)

template <int O, int TB = 1>
__device__ __forceinline__ void wgmma128(float (&a)[128], uint32_t da, uint32_t db, int scale_d) {
    asm volatile(
        "{\n.reg .pred p;\n.reg .b64 da, db;\nsetp.ne.b32 p, %66, 0;\n"
        "mov.b64 da, {%64, 0x40000040};\nmov.b64 db, {%65, %68};\n"
        "wgmma.mma_async.sync.aligned.m64n128k16.f32.bf16.bf16 "
        "{%0,%1,%2,%3,%4,%5,%6,%7,%8,%9,%10,%11,%12,%13,%14,%15,"
        "%16,%17,%18,%19,%20,%21,%22,%23,%24,%25,%26,%27,%28,%29,%30,%31,"
        "%32,%33,%34,%35,%36,%37,%38,%39,%40,%41,%42,%43,%44,%45,%46,%47,"
        "%48,%49,%50,%51,%52,%53,%54,%55,%56,%57,%58,%59,%60,%61,%62,%63},"
        "da, db, p, 1, 1, 0, %67;\n}"
        : R64(a, O)
        : "r"(da), "r"(db), "r"(scale_d), "n"(TB), "n"(TB ? 0x80000020 : 0x40000040));
}
template <int O>
__device__ __forceinline__ void wgmma128_k8(float (&a)[128], uint32_t da, uint32_t db) {
    asm volatile(
        "{\n.reg .b64 da, db;\nmov.b64 da, {%64, 8};\nmov.b64 db, {%65, 8};\n"
        "wgmma.mma_async.sync.aligned.m64n128k16.f32.bf16.bf16 "
        "{%0,%1,%2,%3,%4,%5,%6,%7,%8,%9,%10,%11,%12,%13,%14,%15,"
        "%16,%17,%18,%19,%20,%21,%22,%23,%24,%25,%26,%27,%28,%29,%30,%31,"
        "%32,%33,%34,%35,%36,%37,%38,%39,%40,%41,%42,%43,%44,%45,%46,%47,"
        "%48,%49,%50,%51,%52,%53,%54,%55,%56,%57,%58,%59,%60,%61,%62,%63},"
        "da, db, 1, 1, 1, 0, 0;\n}"
        : R64(a, O)
        : "r"(da), "r"(db));
}
template <int O>
__device__ __forceinline__ void fence_regs64(float (&a)[128]) {
    asm volatile("" : R64(a, O)::"memory");
}

struct Params {
    const __nv_bfloat16* x;
    const __nv_bfloat16* dre;
    const __nv_bfloat16* dim;
    const __nv_bfloat16* cre;
    const __nv_bfloat16* cim;
    const __nv_bfloat16* wr;
    const __nv_bfloat16* wg;
    const __nv_bfloat16* wu;
    const __nv_bfloat16* wd;
    __nv_bfloat16* out;
    Scratch* scr;
};

__device__ __forceinline__ float warp_sum(float v) {
#pragma unroll
    for (int o = 16; o; o >>= 1) v += __shfl_xor_sync(0xffffffffu, v, o);
    return v;
}
__device__ __forceinline__ float sum8(const uint4& v) {
    return ((bf_lo(v.x) + bf_hi(v.x)) + (bf_lo(v.y) + bf_hi(v.y))) + ((bf_lo(v.z) + bf_hi(v.z)) + (bf_lo(v.w) + bf_hi(v.w)));
}
__device__ __forceinline__ void fma8(float* acc, const uint4& w, float s) {
    acc[0] = fmaf(s, bf_lo(w.x), acc[0]); acc[1] = fmaf(s, bf_hi(w.x), acc[1]); acc[2] = fmaf(s, bf_lo(w.y), acc[2]); acc[3] = fmaf(s, bf_hi(w.y), acc[3]);
    acc[4] = fmaf(s, bf_lo(w.z), acc[4]); acc[5] = fmaf(s, bf_hi(w.z), acc[5]); acc[6] = fmaf(s, bf_lo(w.w), acc[6]); acc[7] = fmaf(s, bf_hi(w.w), acc[7]);
}
__device__ __forceinline__ int tid_now() { int t; asm volatile("mov.u32 %0, %%tid.x;" : "=r"(t)); return t; }

#define GAP(...) do { asm volatile("" : __VA_ARGS__); \
    asm volatile("{\n.reg .pred p;\n.reg .b32 t;\nL: mov.u32 t, %clock_hi;\nsetp.eq.u32 p, t, 0xffffffff;\n@p bra L;\n}"); } while (0)
#define ONCE(...) do { int z_ = one; _Pragma("unroll 1") do { __VA_ARGS__ } while (--z_); } while (0)
__device__ __forceinline__ unsigned clk() { unsigned t; asm volatile("mov.u32 %0, %%clock;" : "=r"(t)); return t; }
__device__ __forceinline__ unsigned keep(unsigned t) { return __shfl_sync(0xffffffffu, t + (threadIdx.x & 31), 0); }
__device__ __forceinline__ void wait_until(unsigned t) { while ((int)(clk() - t) < 0) { if (WSL) __nanosleep(WSL); } }

__device__ __forceinline__ void spare_cta(const Params& P, uint8_t* smem, uint32_t sb, int tid, int warp, int b) {
    const unsigned dl = keep(clk_hi() + 1);
    const unsigned t_in = keep(clk());
    unsigned t0 = t_in + I0;
    const int lane = tid & 31, e = b - NCTA;
    const unsigned ep = load_epoch(&P.scr->epoch2[e].x);
    const char* dsrc = reinterpret_cast<const char*>(((e >> 1) ? P.dim : P.dre) + (size_t)((e & 1) * 512 + (warp & 1) * 32 + 12) * D_);
    const char* wsrc = reinterpret_cast<const char*>(((warp & 1) ? P.wu : P.wg) + (size_t)(OWN + e * SLR) * F_);
    const uint64_t pol = policy_evict_first();
    const uint32_t bar = sb + 15872;
    constexpr int last = 8 + SLR / 2;
    float* xn = reinterpret_cast<float*>(smem);
    float* rsum = reinterpret_cast<float*>(smem + 15360);
    if (tid == 0) { for (int i = 0; i < SPW; i++) mbar_init(bar + 8 * i, 1); fence_async_smem(); }
    float ag[16];
#pragma unroll
    for (int i = 0; i < 16; i++) ag[i] = 0.f;
    int slot = 0, ph = 1;
#pragma unroll 1
    for (int n = -SPW; n < last; n++) {
        const uint32_t st = sb + 16384 + slot * 32768;
        if (n == 8) {
            if (warp == 15) {
                uint4 f;
                wait_until(t_in + BPT + 800);
                while (true) {
                    f = ld_relaxed128(&P.scr->best[2 * (e * 32 + (lane & 15))]);
                    if (__all_sync(0xffffffffu, f.w == ep) || !IN_TIME()) break;
                    __nanosleep(100);
                }
                const unsigned key = __reduce_max_sync(0xffffffffu, f.x);
                const int from = __ffs(__ballot_sync(0xffffffffu, f.x == key)) - 1;
                const float m = __uint_as_float(__shfl_sync(0xffffffffu, f.y, from)), ri = __uint_as_float(__shfl_sync(0xffffffffu, f.z, from));
                const uint32_t n0 = norm2(__ldg(reinterpret_cast<const uint32_t*>(P.x + (size_t)(0xffff - (int)(key & 0xffffu)) * D_ + OWN + e * SLR) + (lane & (SLR / 2 - 1))), m, ri);
                *reinterpret_cast<float2*>(xn + lane * 2) = make_float2(bf_lo(n0), bf_hi(n0));
            }
            __syncthreads();
            t0 = clk();
        }
        if (n >= 0) {
            mbar_wait(bar + 8 * slot, ph);
            if (n < 8) {
                float a0 = 0.f;
#pragma unroll 1
                for (int i = 0; i < 4; i++) a0 += sum8(lds128(st + warp * 2048 + i * 512 + lane * 16));
                a0 = warp_sum(a0);
                if (lane == 0) rsum[n * 16 + warp] = a0;
            } else if (warp < 14) {
                const float2 x2 = *reinterpret_cast<const float2*>(xn + (n - 8) * 2);
#pragma unroll
                for (int i = 0; i < 4; i++) fma8(ag + 8 * (i >> 1), lds128(st + i * 7168 + tid * 16), (i & 1) ? x2.y : x2.x);
            }
        }
        __syncthreads();
        if ((unsigned)n < 8 && tid < 16)
            st_relaxed64(&P.scr->rs[(e >> 1) * D_ + (e & 1) * 512 + (n * 4 + (tid >> 2)) * 16 + 12 + (tid & 3)], __float_as_uint(rsum[n * 16 + tid]), ep);
        const int m = n + SPW;
        if (m < last && warp >= 14) {
            while ((int)(clk() - t0) < 0) {}
            t0 += SPG;
            if (elect_one()) {
                if (warp == 14) mbar_expect_tx(bar + 8 * slot, m < 8 ? 32768 : 28672);
                if (m < 8) {
                    bulk_g2s(st + (warp & 1) * 16384, dsrc + (size_t)m * 64 * 2 * D_, 8192, bar + 8 * slot);
                    bulk_g2s(st + (warp & 1) * 16384 + 8192, dsrc + (size_t)(m * 64 + 16) * 2 * D_, 8192, bar + 8 * slot);
                } else {
                    asm volatile("cp.async.bulk.shared::cluster.global.mbarrier::complete_tx::bytes.L2::cache_hint [%0], [%1], %2, [%3], %4;"
                                 ::"r"(st + (warp & 1) * 14336), "l"(wsrc + (size_t)(m - 8) * 4 * F_), "r"(14336), "r"(bar + 8 * slot), "l"(pol) : "memory");
                }
            }
            __syncwarp();
        }
        if (++slot == SPW) { slot = 0; ph ^= 1; }
    }
    if (warp < 14) {
        float4* ps = reinterpret_cast<float4*>(smem + 16384) + tid * 2;
#pragma unroll
        for (int i = 0; i < 4; i++) ps[(i >> 1) * (F_ / 4) + (i & 1)] = make_float4(ag[4 * i], ag[4 * i + 1], ag[4 * i + 2], ag[4 * i + 3]);
    }
    __syncthreads();
    const uint32_t* ps = reinterpret_cast<const uint32_t*>(smem + 16384);
#pragma unroll 1
    for (int f = tid; f < F_; f += NTHREADS) st_relaxed128(&P.scr->gu[e * F_ + f], make_uint4(ps[f], ps[F_ + f], ep, 0));
    if (tid == 0) P.scr->epoch2[e].x = ep;
}

__global__ void __cluster_dims__(2, 1, 1) __launch_bounds__(NTHREADS, 1)
fnet_fused_kernel(const __grid_constant__ CUtensorMap tm_x, const __grid_constant__ CUtensorMap tm_dre,
                  const __grid_constant__ CUtensorMap tm_dim, const __grid_constant__ CUtensorMap tm_cre,
                  const __grid_constant__ CUtensorMap tm_cim, const Params P) {
    extern __shared__ __align__(1024) uint8_t smem_[];
    const int tid = threadIdx.x, lane = tid & 31;
    int b;
    {
        unsigned sm; asm volatile("mov.u32 %0, %%smid;" : "=r"(sm));
        const int t = sm >> 1, u = t - 32;
        const int pr = u < 0 ? t : u < 28 ? t + 1 + ((u * 37) >> 8) : u < 30 ? t + 4 : (t - 58) * 8;
        b = pr * 2 + (blockIdx.x & 1);
    }
    const int c = b & 1;
    const uint32_t sb = SB0 | (c << 24);
    uint8_t* const smem = reinterpret_cast<uint8_t*>(__cvta_shared_to_generic(sb));
    const int grp = b >> 4;
    const int part = grp & 1;
    const int eb = grp >> 1;
    const int j = b & 15;
    const int sh = eb != 0;
    const int ci = b >> 1;
    const bool moe = b < NMOE;
#define KBLK(it) ((it) <= 4 ? (4 * eb - sh + (it)) ^ sh : 4 * eb - sh + (it) - (4 * eb - sh + (it) > 15 ? 15 : 0))
    const uint32_t bar0 = sb + OFF_BAR;
#define BAR(i) (bar0 + 8u * (i))
#define CLUSTER_ARRIVE() asm volatile("barrier.cluster.arrive.relaxed.aligned;" ::: "memory")
#define CLUSTER_WAIT() asm volatile("barrier.cluster.wait.aligned;" ::: "memory")
#define FENCE_INIT() asm volatile("fence.mbarrier_init.release.cluster;" ::: "memory")
#define TE(i)
    const int warp = __shfl_sync(0xffffffffu, tid >> 5, 0);
    TE(0);
    if (warp == 0 && elect_one()) {
#pragma unroll
        for (int s = 0; s < 4; s++) mbar_init(BAR(B_FULL + s), 1);
        FENCE_INIT();
    }
    __syncwarp();
    CLUSTER_ARRIVE();
    TE(1);
    if (warp == 1 && elect_one()) prefetch_tmap(part ? &tm_dim : &tm_dre);
    const bool first = warp == 0 && b < NCTA;
    if (first && elect_one()) {
        mbar_expect_tx(BAR(B_FULL + 0), STAGE_BYTES);
        tma_2d(sb, &tm_x, 0, j * 128, BAR(B_FULL + 0));
    }
    __syncwarp();
    TE(2);
    CLUSTER_WAIT();
    TE(3);
    if (first && elect_one()) tma_2d_mc(sb + A_BYTES + c * 16384, part ? &tm_dim : &tm_dre, 0, eb * 256 + 128 * (c ^ part), BAR(B_FULL + 0));
    __syncwarp();
    const unsigned t_first = keep(clk());
    if ((warp == 3 || warp == 12) && elect_one()) {
        if (warp != 3) {
#pragma unroll
            for (int s = B_EMPTY; s < 20; s++) mbar_init(BAR(s), bar_count(s));
        } else {
#pragma unroll
            for (int s = 20; s < B_COUNT; s++) mbar_init(BAR(s), bar_count(s));
            *reinterpret_cast<uint4*>(smem + OFF_MIR) = make_uint4(0, 0, 0, 0);
        }
        FENCE_INIT();
    }
    __syncwarp();
    if (warp == 12 && b < NCTA) {
        named_arrive<0, NTHREADS>();
        if (elect_one()) {
            mbar_expect_tx(BAR(B_FULL + 1), STAGE_BYTES);
            while ((int)(clk() - t_first) < PACE1) {}
            tma_2d(sb + STAGE_BYTES, &tm_x, KBLK(1) * 64, j * 128, BAR(B_FULL + 1));
            tma_2d_mc(sb + STAGE_BYTES + A_BYTES + c * 16384, part ? &tm_dim : &tm_dre, KBLK(1) * 64, eb * 256 + 128 * (c ^ part), BAR(B_FULL + 1));
        }
        __syncwarp();
    } else {
        named_bar<0, NTHREADS>();
    }
    if (__popc(smem_u32(smem_) ^ sb) > blockIdx.y) return;
    if (__builtin_expect(b >= NCTA, 0)) { spare_cta(P, smem, sb, tid, warp, b); return; }

    const unsigned dl = keep(clk_hi() + 1);
    if (warp >= 12) {
        asm volatile("setmaxnreg.dec.sync.aligned.u32 %0;" ::"n"(PROD_REGS));
        if (warp == 12) {
            const CUtensorMap* tmD = part ? &tm_dim : &tm_dre;
            const CUtensorMap* tmC = part ? &tm_cim : &tm_cre;
            const int row0 = j * 128, drow = eb * 256 + 128 * (c ^ part), q0 = j >> 1;
            if (elect_one()) {
                const unsigned t0 = t_first;
#pragma unroll 1
                for (int it = 2; it < 16; it++) {
                    const int s = it & 3;
                    const uint32_t st = sb + s * STAGE_BYTES, fb = BAR(B_FULL + s);
                    if (it < 4) {
                        wait_until(t0 + (it == 2 ? PACE2 : PACE3));
                    } else {
                        mbar_wait(BAR(B_EMPTY + s), ((it >> 2) & 1) ^ 1);
                        if (it < 8 + sh) mbar_wait(BAR(B_HRD + it - 4), 0);
                    }
                    mbar_expect_tx(fb, STAGE_BYTES);
                    const int kc = KBLK(it) * 64;
                    tma_2d(st, &tm_x, kc, row0, fb);
                    tma_2d_mc(st + A_BYTES + c * 16384, tmD, kc, drow, fb);
                    TRACE(128 + it);
                    if (it == 4) { prefetch_tmap(&tm_cre); prefetch_tmap(&tm_cim); }
                }
                const unsigned ep = load_epoch(&P.scr->epoch[b]);
#pragma unroll 1
                for (int i = 0; i < 2; i++) {
                    mbar_wait(BAR(B_EMPTY + i), 1);
                    mbar_expect_tx(BAR(B_FULL + i), A_BYTES);
                    tma_2d(sb + i * STAGE_BYTES, tmC, (2 * j + i) * 64, row0, BAR(B_FULL + i));
                    TRACE(128 + 16 + i);
                }
                const uint8_t* abg = P.scr->ab + (size_t)grp * 32 * B_BYTES;
                int it = 18;
                unsigned have = 0;
                auto seen = [&](int word, unsigned want) {
                    if ((have & want) == want) return;
                    do {
                        asm volatile("ld.acquire.cta.shared::cta.u32 %0, [%1];" : "=r"(have) : "r"(sb + OFF_MIR + 4 * word) : "memory");
                    } while ((have & want) != want && IN_TIME());
                    asm volatile("fence.proxy.async.global;" ::: "memory");
                };
                unsigned long long rdy = (unsigned long long)(~ep & 0xffu) * 0x0101010101010101ull;
#pragma unroll 1
                for (int cl = 0; cl < 4; cl++) {
                    const int ko = ((cl & 1) << 1) + (cl >> 1);
#pragma unroll 1
                    for (int n = cl < 2; n < (cl < 3 ? 8 : 8 - RS); n++, it++) {
                        const int q = (q0 + n) & 7, kb = n ? 4 * q + ko : 2 * (j ^ 1) + cl - 2;
                        const int s = it & 3;
                        const uint32_t fb = BAR(B_FULL + s), bs = sb + b2_off(s);
                        if (it != 19) {
                            mbar_wait(BAR(B_EMPTY + s), ((it >> 2) & 1) ^ 1); mbar_expect_tx(fb, STAGE_BYTES);
                            tma_2d(sb + s * STAGE_BYTES, tmC, kb * 64, row0, fb);
                        }
                        if (it == 18) {
                            mbar_wait(BAR(B_EMPTY + 3), 1); mbar_expect_tx(BAR(B_FULL + 3), STAGE_BYTES);
                            tma_2d(sb + 3 * STAGE_BYTES, tmC, ((q + 1) & 7) * 256, row0, BAR(B_FULL + 3));
                        }
                        if (cl == 0) {
                            if (((unsigned)(rdy >> (8 * q)) & 0xffu) != (ep & 0xffu)) {
                                do { rdy = ld_relaxed64(&P.scr->abflag[grp * 16]); } while (((unsigned)(rdy >> (8 * q)) & 0xffu) != (ep & 0xffu) && IN_TIME());
                                asm volatile("fence.acquire.gpu;\nfence.proxy.async.global;" ::: "memory");
                            }
                        } else {
                            seen(0, 1u << (8 * (n ? cl : 2 * cl - 3 - c) + q));
                        }
                        if (it == 18) TRACE(199);
                        if (n) bulk_g2s_mc(bs + c * 16384, abg + (size_t)kb * B_BYTES + c * 16384, 16384, fb);
                        else bulk_g2s(bs, abg + (size_t)kb * B_BYTES, B_BYTES, fb);
                        *reinterpret_cast<volatile int*>(smem + OFF_MIR + 8) = it;
                        TRACE(128 + it);
                    }
                }
                have = 0;
                seen(1, 0xff000000u);
                const uint8_t* abf = P.scr->ab + (size_t)(grp ^ 1) * 32 * B_BYTES + 16384;
                const uint8_t* const ab0 = (part ^ HORD) ? abf : abg;
                const uint8_t* const ab1 = (part ^ HORD) ? abg : abf;
                const CUtensorMap* const tm0 = HORD ? &tm_cim : &tm_cre;
                const CUtensorMap* const tm1 = HORD ? &tm_cre : &tm_cim;
#define AB0 ab0
#define AB1 ab1
                mbar_wait(BAR(B_SPF), 0);
#pragma unroll
                for (int h = 0; h < NH; h++) {
                    const int kb = 4 * ((q0 + 8 - RS + (h >> 1)) & 7) + 3;
                    const uint32_t fb = BAR(hf_bar(h));
                    if (h >= 7) mbar_wait(BAR(he_bar(h - 7)), he_par(h - 7));
                    else if (h != 1 && h != 3 && h != 6) { const int i = h == 5 ? 3 : h >> 1; mbar_wait(BAR(B_EMPTY + hs(i)), hp(i) ^ 1); }
                    mbar_expect_tx(fb, 32768);
                    tma_2d(sb + ha_off(h), (h & 1) ? tm1 : tm0, kb * 64, row0, fb);
                    bulk_g2s_mc(sb + hb_off(h) + c * 8192, ((h & 1) ? AB1 : AB0) + (size_t)kb * B_BYTES + c * 8192, 8192, fb);
                    if (h == NH - FRSH) *reinterpret_cast<volatile int*>(smem + OFF_MIR + 8) = FRS;
                    TRACE(128 + 48 - RS + h);
                }
                P.scr->epoch[b] = ep;
            }
        } else {
          const unsigned t_in = t_first;
          const unsigned ep = load_epoch(&P.scr->epoch[b]);
          {
            if (lane == 0) TRACE(227);
#pragma unroll 1
            for (int k = -DLAG; k < 4; k++) {
                const int r = 4 * (warp - 13) + k;
                if (k + DLAG < 4) {
                    wait_until(t_in + D0 + (k + DLAG) * DGAP);
                    if (elect_one()) {
                        mbar_expect_tx(BAR(B_DR + k + DLAG), 2048);
                        bulk_g2s(sb + OFF_X + (r + DLAG) * 2048, (part ? P.dim : P.dre) + (size_t)(eb * 256 + j * 16 + r + DLAG) * D_, 2048, BAR(B_DR + k + DLAG));
                    }
                    __syncwarp();
                }
                if (k < 0) continue;
                mbar_wait_sleep(BAR(B_DR + k), 0);
                if (tid == 13 * 32) TRACE(228 + k);
                uint4 v[4];
#pragma unroll
                for (int i = 0; i < 4; i++) v[i] = lds128(sb + OFF_X + r * 2048 + i * 512 + lane * 16);
                float a0 = 0.f;
#pragma unroll
                for (int i = 0; i < 4; i++) { a0 += sum8(v[i]); if (i & 1) GAP("+f"(a0)); }
                a0 = warp_sum(a0);
                if (lane == 0) reinterpret_cast<float*>(smem + OFF_H)[r] = a0;
            }
#pragma unroll 1
            for (int i = warp - 13; i < CPN; i += 3)
                prefetch_l2((part ? P.cim : P.cre) + (size_t)(j * 128 + eb * 32 + lane) * S_ + (i < 2 ? 2 * j + i : 4 * (((j >> 1) + i - 1) & 7)) * 64);
            if (lane == 0) TRACE(217 + warp - 13);
          }
          if (lane == 0) mbar_arrive(BAR(B_RSD));
          if (warp == 14) {
#define AT_STEP(n) do { while (*reinterpret_cast<volatile int*>(smem + OFF_MIR + 8) < (n) && IN_TIME()) __nanosleep(MSL); } while (0)
#define WATCH(g, word, want) do { const uint8_t* fp = reinterpret_cast<const uint8_t*>(&P.scr->abflag[(g) * 16]) + lane; \
                unsigned known = 0; \
                while (true) { \
                    const unsigned m = __ballot_sync(0xffffffffu, ld_relaxed8(fp) == (ep & 0xffu)); \
                    if (m != known) { \
                        known = m; \
                        asm volatile("fence.acquire.gpu;" ::: "memory"); \
                        __syncwarp(); \
                        if (lane == 0) asm volatile("st.release.cta.shared::cta.u32 [%0], %1;" ::"r"(sb + OFF_MIR + 4 * (word)), "r"(m) : "memory"); \
                    } \
                    if ((m & (want)) == (want) || !IN_TIME()) break; \
                    __nanosleep(MSL); \
                } } while (0)
            AT_STEP(WS0);
            WATCH(grp, 0, 0xffffu);
            if (moe) {
                uint4 g[4];
                const uint4* gp = &P.scr->gu[ci * 64 + c * 32 + lane];
                AT_STEP(GUS);
                while (true) {
                    bool ok = true;
#pragma unroll
                    for (int i = 0; i < 4; i++) { g[i] = ld_relaxed128(gp + i * F_); ok = ok && g[i].z == ep; }
                    if (__all_sync(0xffffffffu, ok) || !IN_TIME()) break;
                    __nanosleep(MSL);
                }
                *reinterpret_cast<float2*>(smem + OFF_RED + lane * 8) =
                    make_float2((__uint_as_float(g[0].x) + __uint_as_float(g[1].x)) + (__uint_as_float(g[2].x) + __uint_as_float(g[3].x)),
                                (__uint_as_float(g[0].y) + __uint_as_float(g[1].y)) + (__uint_as_float(g[2].y) + __uint_as_float(g[3].y)));
                __syncwarp();
                if (lane == 0) { mbar_arrive(BAR(B_GU)); TRACE(223); }
            }
#pragma unroll 1
            for (int k = 0; k < 3; k++) {
                AT_STEP(k == 0 ? WS1 : k == 1 ? WS2 : WS3);
                WATCH(grp ^ (k >> 1), k >> 1, k ? 0xffffffffu : 0xffffffu);
            }
          } else {
           if (warp == 13) {
                uint8_t* dst = smem + OFF_MO;
                mbar_wait(BAR(B_RSD), 0);
                if (lane < 12) st_relaxed64(&P.scr->rs[part * D_ + eb * 256 + j * 16 + lane], reinterpret_cast<const uint32_t*>(smem + OFF_H)[lane], ep);
                wait_until(t_in + RSD);
                if (lane == 0) TRACE(225);
                uint4 f[4];
                bool ok;
#pragma unroll
                for (int i = 0; i < 4; i++) f[i].y = ~ep;
                do {
                    ok = true;
#pragma unroll
                    for (int i = 0; i < 4; i++)
                        if (f[i].y != ep || f[i].w != ep)
                            f[i] = ld_relaxed128(reinterpret_cast<const uint4*>(P.scr->rs) + part * 512 + eb * 128 + 64 * ((i >> 1) ^ part) + (i & 1) * 32 + lane);
#pragma unroll
                    for (int i = 0; i < 4; i++) ok = ok && f[i].y == ep && f[i].w == ep;
                } while (!__all_sync(0xffffffffu, ok) && IN_TIME());
                if (lane == 0) TRACE(226);
#pragma unroll
                for (int i = 0; i < 8; i++) {
                    const float v = 0.5f * __uint_as_float((i & 1) ? f[i >> 1].z : f[i >> 1].x);
                    const float hi = rbf(v), mid = rbf(v - hi), lo = v - hi - mid;
                    *reinterpret_cast<uint4*>(dst + (((i >> 1) * 32 + lane) * 2 + (i & 1)) * 16) = make_uint4(pack_bf(hi, mid), pack_bf(lo, 0.f), 0, 0);
                }
                fence_async_smem();
                __syncwarp();
                if (lane == 0) { mbar_arrive(BAR(B_STATS)); TRACE(204); }
            }
#define FLAG(w) st_release8(reinterpret_cast<uint8_t*>(&P.scr->abflag[grp * 16 + 2 * (w) + c]) + (j >> 1), ep & 0xffu)
            const int hf = (warp >> 1) & 1;
            if (!hf && elect_one()) {
                mbar_wait(BAR(B_EPI), 0);
                mbar_arrive(BAR(B_HS));
                TRACE(206);
                FLAG(0);
                TRACE(207);
            }
            __syncwarp();
            uint8_t* dst = P.scr->ab + (size_t)(grp * 32 + 2 * j + 1) * B_BYTES + hf * 16384 + lane * 16;
            uint32_t src = sb + OFF_SP + hf * 16384 + lane * 16;
            mbar_wait_sleep(BAR(B_EPI + 3), 0);
            unsigned t0 = clk() + (c ? DELAY2 : DELAY0);
#pragma unroll 1
            for (int i = 0; i < 8; i++, src += 2048, dst += 2048, t0 += SPACE0) {
                wait_until(t0);
                uint4 v[4];
#pragma unroll
                for (int u = 0; u < 4; u++) v[u] = lds128(src + u * 512);
#pragma unroll
                for (int u = 0; u < 4; u++) stg128(dst + u * 512, v[u].x, v[u].y, v[u].z, v[u].w);
            }
            named_bar<3, 64>();
            if (!hf && elect_one()) {
                mbar_arrive(BAR(B_SPF));
                TRACE(209);
                FLAG(1);
                TRACE(210);
            }
          }
        }
    } else if (warp >= 8) {
        asm volatile("setmaxnreg.dec.sync.aligned.u32 %0;" ::"n"(HELP_REGS));
        const int aw = warp - 8, mt = tid - 256;
        float* hact = reinterpret_cast<float*>(smem + OFF_H);
        uint4 buf[NB];
#define WP0() reinterpret_cast<const char*>(((aw & 1) ? P.wu : P.wg) + (size_t)(c * (OWN / 2) + (aw >> 1) * (OWN / 4) + ((tid_now() >> 3) & 3)) * F_ + ci * 64 + (tid_now() & 7) * 8)
        {
            const unsigned t_in = t_first;
            const unsigned ep = load_epoch(&P.scr->epoch[b]);
            uint4 w[4];
            w[0] = __ldg(reinterpret_cast<const uint4*>(P.wr + eb * 256 + lane * 8));
            float s1[4], s2[4], sx[4];
#pragma unroll
            for (int r = 0; r < 4; r++) { s1[r] = 0.f; s2[r] = 0.f; sx[r] = 0.f; }
            const int xr0 = part * 64 + aw * 16 + (lane >> 3);
            const uint32_t xa0 = sb + xr0 * 128 + (((lane & 7) ^ (lane >> 3)) << 4);
            if (sh) { mbar_wait_sleep(BAR(B_FULL), 0); if (lane < 3) mbar_arrive(BAR(B_HRD)); }
#pragma unroll 1
            for (int s = sh; s < sh + 4; s++) {
                const int from = ((s - sh) ^ sh) * 8 + (lane & 7);
                const uint4 wn = make_uint4(__shfl_sync(0xffffffffu, w[0].x, from), __shfl_sync(0xffffffffu, w[0].y, from),
                                            __shfl_sync(0xffffffffu, w[0].z, from), __shfl_sync(0xffffffffu, w[0].w, from));
                const float wf[8] = {bf_lo(wn.x), bf_hi(wn.x), bf_lo(wn.y), bf_hi(wn.y), bf_lo(wn.z), bf_hi(wn.z), bf_lo(wn.w), bf_hi(wn.w)};
                mbar_wait_sleep(BAR(B_FULL + (s & 3)), s >> 2);
                const uint32_t xa = xa0 + (s & 3) * STAGE_BYTES;
                uint4 v[4];
#pragma unroll
                for (int r = 0; r < 4; r++) v[r] = lds128((xa ^ ((r & 1) << 6)) + r * 512);
                if (lane < (((s - sh) >> 1) == part ? 1 : 3)) mbar_arrive_after(BAR(B_HRD + s), v[0].x | v[1].x | v[2].x | v[3].x);
#pragma unroll
                for (int r = 0; r < 4; r++) {
                    const uint32_t xv[4] = {v[r].x, v[r].y, v[r].z, v[r].w};
#pragma unroll
                    for (int e = 0; e < 4; e++) {
                        const float a0 = bf_lo(xv[e]), a1 = bf_hi(xv[e]);
                        s1[r] += a0; s1[r] += a1;
                        s2[r] = fmaf(a1, a1, fmaf(a0, a0, s2[r]));
                        sx[r] = fmaf(a1, wf[2 * e + 1], fmaf(a0, wf[2 * e], sx[r]));
                    }
                    GAP("+f"(s1[r]), "+f"(s2[r]), "+f"(sx[r]));
                }
            }
            if (mt == 0) TRACE(211);
#pragma unroll
            for (int i = 1; i < 4; i++) w[i] = __ldg(reinterpret_cast<const uint4*>(P.wr + (eb ^ i) * 256 + lane * 8));
#define FOLD4(a, H, L) do { const bool uh = lane & (H), ul = lane & (L); \
                float p0 = (uh ? a[2] : a[0]) + __shfl_xor_sync(0xffffffffu, uh ? a[0] : a[2], H); \
                float p1 = (uh ? a[3] : a[1]) + __shfl_xor_sync(0xffffffffu, uh ? a[1] : a[3], H); \
                a[0] = (ul ? p1 : p0) + __shfl_xor_sync(0xffffffffu, ul ? p0 : p1, L); \
                _Pragma("unroll") for (int o = (L) >> 1; o; o >>= 1) a[0] += __shfl_xor_sync(0xffffffffu, a[0], o); } while (0)
            FOLD4(s1, 4, 2); FOLD4(s2, 4, 2); FOLD4(sx, 4, 2);
            if (!(lane & 1))
                st_relaxed128(&P.scr->xp[eb * S_ + j * 128 + xr0 + ((lane & 6) << 1)],
                              make_uint4(__float_as_uint(s1[0]), __float_as_uint(fmaf(s1[0] * (-1.0f / 256), s1[0], s2[0])), __float_as_uint(sx[0]), ep));
            wait_until(clk() + XPD);
            wait_until(t_in + XPT);
            {
                uint4 f[4];
                const uint4* xp = &P.scr->xp[j * 128 + mt];
                bool ok;
#pragma unroll
                for (int i = 0; i < 4; i++) f[i] = ld_relaxed128(xp + i * S_);
                float sw = sum8(w[0]) + sum8(w[1]), sw2;
                GAP("+f"(sw));
                sw2 = sum8(w[2]) + sum8(w[3]);
                GAP("+f"(sw2));
                sw = warp_sum(sw + sw2);
                do {
#pragma unroll
                    for (int i = 0; i < 4; i++) if (f[i].w != ep) f[i] = ld_relaxed128(xp + i * S_);
                    ok = f[0].w == ep && f[1].w == ep && f[2].w == ep && f[3].w == ep;
                } while (!__all_sync(0xffffffffu, ok) && IN_TIME());
                if (mt == 0) TRACE(224);
                const float mean = ((__uint_as_float(f[0].x) + __uint_as_float(f[1].x)) + (__uint_as_float(f[2].x) + __uint_as_float(f[3].x))) * (1.0f / D_);
                float m2 = 0.f, px = 0.f;
#pragma unroll
                for (int i = 0; i < 4; i++) {
                    const float d = fmaf(__uint_as_float(f[i].x), 1.0f / 256, -mean);
                    m2 += fmaf(d * 256.f, d, __uint_as_float(f[i].y));
                    px += __uint_as_float(f[i].z);
                }
                const float mb = rbf(mean);
                float sd, rinv;
                asm("sqrt.approx.ftz.f32 %0, %1;" : "=f"(sd) : "f"(rbf(rbf(fmaxf(m2 * (1.0f / D_), 0.f)) + 1e-5f)));
                asm("rcp.approx.ftz.f32 %0, %1;" : "=f"(rinv) : "f"(rbf(sd)));
                unsigned u = pack_bf(fmaf(-mb, sw, px) * rinv, 0.f);
                u = (u & 0x8000u) ? (~u & 0xffffu) : (u | 0x8000u);
                u = (u << 16) | (0xffffu - (unsigned)(j * 128 + mt));
                if (u == __reduce_max_sync(0xffffffffu, u))
                    *reinterpret_cast<uint4*>(smem + OFF_RED + aw * 16) = make_uint4(u, __float_as_uint(mb), __float_as_uint(rinv), 0);
                named_bar<4, 128>();
                if (aw == 0) {
                    const uint4 g = *reinterpret_cast<const uint4*>(smem + OFF_RED + (lane & 3) * 16);
                    if (g.x == __reduce_max_sync(0xffffffffu, g.x) && lane < 8) st_relaxed128(&P.scr->best[2 * b + (lane >> 2)], make_uint4(g.x, g.y, g.z, ep));
                }
                if (mt == 0) TRACE(212);
                *reinterpret_cast<float2*>(smem + OFF_MO + 4096 + mt * 8) = make_float2(mb, rinv);
                sts128(sb + OFF_MO + 5120 + mt * 16, pack_bf(-mb, -mb), pack_bf(-mb, 0.f), 0, 0);
                fence_async_smem();
                __syncwarp();
                if (lane == 0) mbar_arrive(BAR(B_STATS));
            }
            if (aw == 0) {
                uint4 f;
                wait_until(t_in + BPT);
                do { f = ld_relaxed128(&P.scr->best[2 * (grp * 16 + (lane & 15))]); } while (!__all_sync(0xffffffffu, f.w == ep) && IN_TIME());
                const unsigned key = __reduce_max_sync(0xffffffffu, f.x);
                if (lane < 16 && f.x == key) { *reinterpret_cast<uint4*>(smem + OFF_SEL) = f; mbar_arrive(BAR(B_SEL)); TRACE(200); }
                __syncwarp();
            }
        }
        if (moe) {
            const uint64_t pol = policy_evict_first();
            mbar_wait(BAR(B_SEL), 0);
            {
                const uint4 sl = lds128(sb + OFF_SEL);
                const float m = __uint_as_float(sl.y), ri = __uint_as_float(sl.z);
                const uint2 xv = __ldg(reinterpret_cast<const uint2*>(P.x + (size_t)(0xffff - (int)(sl.x & 0xffffu)) * D_ + c * (OWN / 2) + mt * 4));
                const char* w0 = WP0();
#pragma unroll
                for (int q = 0; q < NB; q++) buf[q] = ldg_stream(w0 + q * 8 * F_, pol);
                const uint32_t n0 = norm2(xv.x, m, ri), n1 = norm2(xv.y, m, ri);
                float* xn = reinterpret_cast<float*>(smem + OFF_XN) + mt;
                xn[0] = bf_lo(n0); xn[132] = bf_hi(n0); xn[264] = bf_lo(n1); xn[396] = bf_hi(n1);
            }
            named_bar<4, 128>();
            float ag[8];
#pragma unroll
            for (int i = 0; i < 8; i++) ag[i] = 0.f;
            uint32_t xq = sb + OFF_XN + (lane >> 3) * 528 + (aw >> 1) * (OWN / 4);
            uint32_t str = 8 * F_;
            const char* wp = WP0() + NB * 8 * F_;
            if (mt == 0) TRACE(213);
            mbar_wait_sleep(BAR(B_EPI + 3), 0);
            wait_until(clk() + GOD);
#pragma unroll 1
            for (int r = 0; r < GR + 4; r++, xq += 32) {
                if (r == GR - 1) { wp = reinterpret_cast<const char*>(P.wd + (size_t)(ci * 64 + c * 32) * D_ + (tid_now() - 256) * 8); str = 2 * D_; }
                if (r == GR + 3) str = 0;
#pragma unroll
                for (int h = 0; h < NB; h += 4) {
                    const uint4 m4 = lds128(xq + h * 4);
                    const uint32_t mv[4] = {m4.x, m4.y, m4.z, m4.w};
#pragma unroll
                    for (int q = 0; q < 4; q++) {
                        fma8(ag, buf[h + q], __uint_as_float(mv[q]));
                        GAP(R8(ag, 0));
                        ldg_stream_next(buf[h + q], wp, str, pol);
                    }
                }
                if (r != GR - 1) continue;
                const int lane = tid_now() & 31;
            {
                const bool uh = lane & 16, ul = lane & 8;
#pragma unroll
                for (int i = 0; i < 4; i++) ag[i] = (uh ? ag[i + 4] : ag[i]) + __shfl_xor_sync(0xffffffffu, uh ? ag[i] : ag[i + 4], 16);
#pragma unroll
                for (int i = 0; i < 2; i++) ag[i] = (ul ? ag[i + 2] : ag[i]) + __shfl_xor_sync(0xffffffffu, ul ? ag[i] : ag[i + 2], 8);
            }
            named_bar<4, 128>();
            float* ps = reinterpret_cast<float*>(smem + OFF_XN);
            *reinterpret_cast<float2*>(&ps[aw * 64 + (lane & 7) * 8 + (lane >> 3) * 2]) = make_float2(ag[0], ag[1]);
            named_bar<4, 128>();
            if (aw == 0) {
                const int o = (c ^ 1) * 32 + lane, m = c * 32 + lane;
                if (lane == 0) { mbar_expect_tx(BAR(B_PEER), 256); mbar_expect_tx(BAR(B_PR2), 2048); }
                const float go = ps[m] + ps[128 + m], uo = ps[64 + m] + ps[192 + m], gx = ps[o] + ps[128 + o], ux = ps[64 + o] + ps[192 + o];
                __syncwarp();
                st_async2(mapa(sb + OFF_RED + 256 + lane * 8, c ^ 1), gx, ux, mapa(BAR(B_PEER), c ^ 1));
                mbar_wait(BAR(B_GU), 0);
                mbar_wait_cluster(BAR(B_PEER), 0);
                const float2 pv = *reinterpret_cast<const float2*>(smem + OFF_RED + 256 + lane * 8);
                const float2 pq = *reinterpret_cast<const float2*>(smem + OFF_RED + lane * 8);
                hact[lane] = rbf(rbf(silu_f(rbf((go + pv.x) + pq.x))) * rbf((uo + pv.y) + pq.y));
                if (lane == 0) TRACE(214);
            }
            named_bar<4, 128>();
#pragma unroll
            for (int i = 0; i < 8; i++) ag[i] = 0.f;
            xq = sb + OFF_H - 32;
            }
            const int mt = tid_now() - 256;
            const unsigned ep = lds128(sb + OFF_SEL).w;
            if ((aw >> 1) != c) {
                const uint32_t rem = mapa(sb + OFF_XN + (mt & 63) * 16, c ^ 1);
                st_async4(rem, ag[0], ag[1], ag[2], ag[3], mapa(BAR(B_PR2), c ^ 1));
                st_async4(rem + 1024, ag[4], ag[5], ag[6], ag[7], mapa(BAR(B_PR2), c ^ 1));
                uint4* clr = &P.scr->part[(((ep + 1) & 1) * (NMOE / 2) + ci) * (D_ / 4) + mt];
                st_relaxed128(clr, make_uint4(0, 0, 0, 0));
                st_relaxed128(clr + 128, make_uint4(0, 0, 0, 0));
            } else {
                mbar_wait_cluster(BAR(B_PR2), 0);
                const float4 p0 = *reinterpret_cast<const float4*>(smem + OFF_XN + (mt & 63) * 16);
                const float4 p1 = *reinterpret_cast<const float4*>(smem + OFF_XN + 1024 + (mt & 63) * 16);
                uint4* dst = &P.scr->part[((ep & 1) * (NMOE / 2) + ci) * (D_ / 4) + mt];
                st_relaxed128(dst, make_uint4(~__float_as_uint(ag[0] + p0.x), __float_as_uint(ag[1] + p0.y), __float_as_uint(ag[2] + p0.z), __float_as_uint(ag[3] + p0.w)));
                st_relaxed128(dst + 128, make_uint4(~__float_as_uint(ag[4] + p1.x), __float_as_uint(ag[5] + p1.y), __float_as_uint(ag[6] + p1.z), __float_as_uint(ag[7] + p1.w)));
            }
            if (mt == 0) TRACE(215);
        }
        mbar_wait_sleep(BAR(B_SEL), 0);
        const uint4 sl = lds128(sb + OFF_SEL);
        const unsigned key = sl.x, ep = sl.w;
        const int sel = 0xffff - (int)(key & 0xffffu);
        const float2 st = make_float2(__uint_as_float(sl.y), __uint_as_float(sl.z));
        if ((sel >> 8) == (j >> 1)) {
            const int lane = tid_now() & 31;
            const uint4* src = &P.scr->part[((ep & 1) * (NMOE / 2) + (c * 4 + aw) * 7) * (D_ / 4) + (lane & 1) * 128 + eb * 32 + part * 16 + (lane >> 1)];
            float4* park = reinterpret_cast<float4*>(smem + OFF_PARK) + lane;
            const uint2 xv = __ldg(reinterpret_cast<const uint2*>(P.x + (size_t)sel * D_ + eb * 256 + part * 128 + lane * 4));
            AT_STEP(FRS);
            uint4 t[7];
#pragma unroll
            for (int u = 0; u < 7; u++) t[u].x = 0;
            bool ok;
            do {
#pragma unroll
                for (int u = 0; u < 7; u++) if (t[u].x == 0) t[u] = ld_relaxed128(src + u * (D_ / 4));
                ok = true;
#pragma unroll
                for (int u = 0; u < 7; u++) ok = ok && t[u].x != 0;
            } while (!__all_sync(0xffffffffu, ok) && IN_TIME());
            float4 a4 = make_float4(0.f, 0.f, 0.f, 0.f);
#pragma unroll
            for (int u = 0; u < 7; u++) {
                a4.x += __uint_as_float(~t[u].x); a4.y += __uint_as_float(t[u].y); a4.z += __uint_as_float(t[u].z); a4.w += __uint_as_float(t[u].w);
            }
            mbar_wait(BAR(he_bar(DEADH)), he_par(DEADH));
            park[aw * 32] = a4;
            named_bar<4, 128>();
            if (aw == 0) {
#pragma unroll
                for (int w = 1; w < 4; w++) { const float4 q = park[w * 32]; a4.x += q.x; a4.y += q.y; a4.z += q.z; a4.w += q.w; }
            }
            if (aw == 0 && (sel >> 7) != j) {
                st_async4(mapa(sb + OFF_RED + lane * 16, c ^ 1), a4.x, a4.y, a4.z, a4.w, mapa(BAR(B_FIN), c ^ 1));
            } else if (aw == 0) {
                if (lane == 0) mbar_expect_tx(BAR(B_FIN), 512);
                unsigned u = key >> 16;
                u = (u & 0x8000u) ? (u & 0x7fffu) : (~u & 0xffffu);
                const float sg = rbf(__fdividef(1.0f, 1.0f + __expf(-__uint_as_float(u << 16))));
                const uint32_t n0 = norm2(xv.x, st.x, st.y), n1 = norm2(xv.y, st.x, st.y);
                mbar_wait_cluster(BAR(B_FIN), 0);
                const float4 q = *reinterpret_cast<const float4*>(smem + OFF_RED + lane * 16);
                a4.x += q.x; a4.y += q.y; a4.z += q.z; a4.w += q.w;
                uint2 o;
                o.x = silu2(pack_bf(bf_lo(n0) + rbf(rbf(a4.x) * sg), bf_hi(n0) + rbf(rbf(a4.y) * sg)));
                o.y = silu2(pack_bf(bf_lo(n1) + rbf(rbf(a4.z) * sg), bf_hi(n1) + rbf(rbf(a4.w) * sg)));
                if (lane == 0) TRACE(216);
                mbar_wait(BAR(B_UPD), 0);
                const uint2 sr = *reinterpret_cast<const uint2*>(smem + OFF_SROW + lane * 8);
                *reinterpret_cast<uint2*>(P.out + (size_t)sel * D_ + eb * 256 + part * 128 + lane * 4) = make_uint2(bfma2(sr.x, o.x, xv.x), bfma2(sr.y, o.y, xv.y));
            }
        }
    } else {
        asm volatile("setmaxnreg.inc.sync.aligned.u32 %0;" ::"n"(CONS_REGS));
        const int wg = warp >> 2, wq = warp & 3;
        const int wt = tid & 127;
#define P4OK 0
        const int one = __shfl_sync(0xffffffffu, blockIdx.y + 1, 0);
        TRACE_C(50);
        float acc[128];
        const uint32_t rel_bar = mapa(BAR(B_EMPTY), (uint32_t)(wt >> 5) & 1);
        const bool rel_thr = (wt == 0) || (wt == 32);
#define RELEASE(s) do { if (rel_thr) mbar_arrive_cluster(rel_bar + 8u * (s)); } while (0)
        const uint32_t dA0 = desc_lo(SB0, 16) + wg * 512;
        constexpr uint32_t dBk0 = desc_lo(SB0 + A_BYTES, 16);
        constexpr uint32_t dBn0 = desc_lo(SB0, 4096);
        constexpr uint32_t ST = STAGE_BYTES >> 4;
        const int row_l = wg * 64 + wq * 16 + (lane >> 2);

        const uint32_t ioff = wq * 1024 + (lane >> 2) * 64 + (((lane & 3) ^ (lane >> 3)) << 4);
        uint32_t sdst = sb + (wg ? OFF_SP : OFF_X) + ioff;
        uint8_t* gdst = P.scr->ab + (size_t)(grp * 32 + 2 * j) * B_BYTES + ioff;
        asm volatile("" : "+l"(gdst), "+r"(sdst));

#define MMA1_H(O, s, first) do { _Pragma("unroll") for (int kk = 0; kk < 4; kk++) \
            wgmma128<O, 0>(acc, dA0 + (s) * ST + kk * 2, dBk0 + (s) * ST + kk * 2 + (O) * 16, !((first) && kk == 0)); } while (0)
#define WAIT_FULL(s, ph, it) do { mbar_wait(BAR(B_FULL + (s)), ph); TRACE_C(it); } while (0)
#define MMA1(s, first, rel) do { wg_fence(); MMA1_H(0, s, first); wg_commit(); wg_wait<1>(); rel; \
            wg_fence(); MMA1_H(64, s, first); wg_commit(); } while (0)
#define WAIT_FULL_L(s, ph, it) WAIT_FULL(s, ph, it)
#define STEP1(s, ph, it, first, rel) do { WAIT_FULL_L(s, ph, it); MMA1(s, first, rel); } while (0)
        uint32_t xr[32];
        const uint32_t xad = sb + row_l * 128 + ((((lane & 4) + (lane & 3)) ^ (lane >> 2)) << 4);
#define XLOAD(s) do { if ((unsigned)(4 * o + (s) - sh - 2 * part) < 2u) { _Pragma("unroll") for (int h = 0; h < 4; h++) { \
            const uint4 u = lds128((xad ^ ((h >> 1) << 6)) + (s) * STAGE_BYTES + (h & 1) * 1024); \
            uint32_t* e = xr + 16 * ((s) & 1) + 4 * h; e[0] = u.x; e[1] = u.y; e[2] = u.z; e[3] = u.w; } \
            } } while (0)
#define XDONE(s) do { if ((unsigned)(4 * o + (s) - sh - 2 * part) < 2u && lane == 0) { const uint32_t* e = xr + 16 * ((s) & 1); \
            mbar_arrive_after(BAR(B_HRD + 4 * o + (s)), e[0] | e[4] | e[8] | e[12]); } } while (0)
#pragma unroll
        for (int i = 0; i < 32; i++) xr[i] = 0;
        TRACE_C(51);
#pragma unroll 1
        for (int o = 0; o < 3; o++) {
            STEP1(0, o & 1, 4 * o, o == 0, if (o) RELEASE(3); XDONE(-1)); XLOAD(0);
            STEP1(1, o & 1, 4 * o + 1, false, RELEASE(0); XDONE(0)); XLOAD(1);
            STEP1(2, o & 1, 4 * o + 2, false, RELEASE(1); XDONE(1)); XLOAD(2);
            STEP1(3, o & 1, 4 * o + 3, false, RELEASE(2); XDONE(2)); XLOAD(3);
        }
#define XSWAP() do { const bool odd = lane & 4; _Pragma("unroll") for (int i = 0; i < 24; i++) if (!(i & 8)) { \
            const uint32_t u0 = xr[i], u1 = xr[i + 8]; xr[i] = odd ? u1 : u0; xr[i + 8] = odd ? u0 : u1; } } while (0)
        XSWAP();
#define MEAN(O) wgmma128_k8<O>(acc, ((SB0 + OFF_MO + 5120) >> 4) + wg * 64, ((SB0 + OFF_MO) >> 4) + 2 * (O))
#define ROWSTAT() do { mbar_wait(BAR(B_STATS), 0); \
            st0 = *reinterpret_cast<const float2*>(smem + OFF_MO + 4096 + row_l * 8); \
            st1 = *reinterpret_cast<const float2*>(smem + OFF_MO + 4096 + row_l * 8 + 64); \
            rs0 = part ? -st0.y : st0.y; rs1 = part ? -st1.y : st1.y; } while (0)
#define PACK1(p, O, i) do { const float rs_ = ((i) & 1) ? rs1 : rs0; _Pragma("unroll") for (int e = 0; e < 4; e++) { \
                const int k = (O) + 16 * ((i) >> 1) + 4 * e + 2 * ((i) & 1); p[4 * (i) + e] = pack_bf(acc[k] * rs_, acc[k + 1] * rs_); } } while (0)
#define IOFF(O, i) ((O) * 256 + ((i) >> 1) * 4096 + ((i) & 1) * 512)
#define STS1(p, O, i) sts128(sdst + IOFF(O, i), p[4 * (i)], p[4 * (i) + 1], p[4 * (i) + 2], p[4 * (i) + 3])
#define STG1(p, O, i) stg128(gdst + IOFF(O, i), p[4 * (i)], p[4 * (i) + 1], p[4 * (i) + 2], p[4 * (i) + 3])
#define PIECES(p, O, G) PIECES_(p, O, G, 0, 8)
#define PIECES_(p, O, G, i0, i1) do { _Pragma("unroll") for (int i = (i0); i < (i1); i += 2) { PACK1(p, O, i); PACK1(p, O, i + 1); \
                ONCE(if (G) { STG1(p, O, i); STG1(p, O, i + 1); } else { STS1(p, O, i); STS1(p, O, i + 1); }); } } while (0)
#define STAGED(i) do { fence_async_smem(); __syncwarp(); if (lane == 0) mbar_arrive(BAR(B_EPI + (i))); } while (0)
        float ac2[128];
#define MMA_F(O, aoff, boff, first) do { wg_fence(); _Pragma("unroll") for (int kk = 0; kk < 4; kk++) \
            wgmma128<O>(ac2, dA0 + ((aoff) >> 4) + kk * 2, dBn0 + ((boff) >> 4) + kk * 64, !((first) && kk == 0)); wg_commit(); } while (0)
#define LEFT16() do { mbar_wait(BAR(B_EPI + 1), 0); WAIT_FULL(0, 0, 16); MMA_F(0, 0, OFF_X, true); } while (0)
        float2 st0, st1;
        float rs0, rs1;
        uint32_t pl[32], pr[32];
        if (wg == 0) {
            STEP1(0, 1, 12, false, RELEASE(3));
            STEP1(1, 1, 13, false, RELEASE(0));
            STEP1(2, 1, 14, false, RELEASE(1));
            ROWSTAT();
            wg_fence(); MEAN(64); MEAN(0);
            WAIT_FULL(3, 1, 15);
            wg_fence(); MMA1_H(0, 3, false); wg_commit();
            MMA1_H(64, 3, false); wg_commit();
            named_arrive<5, 256>();
            const bool pub = c == 0;
            wg_wait<1>();
            fence_regs64<0>(acc);
            TRACE_C(52);
            PIECES(pl, 0, pub);
            TRACE_C(53);
            wg_wait<0>();
            fence_regs64<64>(acc);
            RELEASE(2); RELEASE(3);
            if (tid == 0) mbar_arrive(BAR(B_W0D));
            mbar_wait(BAR(B_W1M), 0);
            TRACE_C(54);
            PIECES(pr, 64, pub);
            if (pub) {
                __syncwarp();
                if (lane == 0) mbar_arrive(BAR(B_EPI + 0));
                mbar_wait(BAR(B_HS), 0);
#pragma unroll
                for (int i = 0; i < 8; i++) STS1(pl, 0, i);
#pragma unroll
                for (int i = 0; i < 8; i++) STS1(pr, 64, i);
            }
            STAGED(1);
            if (!pub) {
#pragma unroll
                for (int i = 0; i < 8; i++) STG1(pl, 0, i);
#pragma unroll
                for (int i = 0; i < 8; i++) STG1(pr, 64, i);
                __syncwarp();
                if (lane == 0) mbar_arrive(BAR(B_EPI + 0));
            }
            LEFT16();
        } else {
            wg_wait<0>(); RELEASE(3);
            ROWSTAT();
            wg_fence(); MEAN(64); MEAN(0); wg_commit();
            wg_wait<0>();
            if (lane == 0) mbar_arrive(BAR(B_W1M));
            named_bar<5, 256>();
            TRACE_C(12);
            wg_fence(); MMA1_H(0, 0, false); MMA1_H(64, 0, false); wg_commit();
            MMA1(1, false, RELEASE(0));
            wg_fence(); MMA1_H(0, 2, false); wg_commit();
            wg_wait<1>(); RELEASE(1);
            wg_fence(); MMA1_H(0, 3, false); wg_commit();
            MMA1_H(64, 2, false); MMA1_H(64, 3, false); wg_commit();
            mbar_wait(BAR(B_W0D), 0);
            wg_wait<1>();
            fence_regs64<0>(acc);
            TRACE_C(52);
            PIECES_(pl, 0, false, 0, 4);
            wg_wait<0>();
            fence_regs64<64>(acc);
            RELEASE(2); RELEASE(3);
            PIECES_(pl, 0, false, 4, 8);
            TRACE_C(53);
            STAGED(2);
            LEFT16();
            TRACE_C(54);
            PIECES(pr, 64, false);
            STAGED(3);
        }
        TRACE_C(55);

#define MMA2K(aoff, boff, k0) do { wg_fence(); _Pragma("unroll") \
        for (int kk = k0; kk < k0 + 2; kk++) { \
            wgmma128<0>(ac2, dA0 + ((aoff) >> 4) + kk * 2, dBn0 + ((boff) >> 4) + kk * 64, 1); \
            wgmma128<64>(ac2, dA0 + ((aoff) >> 4) + kk * 2, dBn0 + ((boff) >> 4) + kk * 64 + 1024, 1); } } while (0)
#define STEP2(s, ph, it) do { WAIT_FULL_L(s, ph, it); MMA2K((s) * STAGE_BYTES, b2_off(s), 0); \
            wg_commit(); wg_wait<1>(); RELEASE(((s) + 3) & 3); \
            MMA2K((s) * STAGE_BYTES, b2_off(s), 2); wg_commit(); } while (0)
#define MMA_H(O, aoff, boff) MMA_F(O, aoff, boff, false)
        MMA_F(64, 0, OFF_X + 16384, true);
        mbar_wait(BAR(B_EPI + 2), 0); mbar_wait(BAR(B_FULL + 1), 0);
        MMA_H(0, STAGE_BYTES, OFF_SP);
        wg_wait<1>(); RELEASE(0);
        mbar_wait(BAR(B_EPI + 3), 0);
        TRACE_C(17);
        MMA_H(64, STAGE_BYTES, OFF_SP + 16384);
        uint32_t g[32];
        const float mr0 = -st0.x * st0.y, mr1 = -st1.x * st1.y;
#define GATE(i) do { _Pragma("unroll") for (int e = (i); e < (i) + 4; e++) { \
                g[16 + e] = gate2(o == GATE_O ? xr[e] : xr[16 + e], ((i) & 4) ? st1.y : st0.y, ((i) & 4) ? mr1 : mr0); \
                g[e] = o == GATE_O ? g[16 + e] : g[e]; } } while (0)
#pragma unroll
        for (int i = 0; i < 32; i++) g[i] = 0;
#pragma unroll 1
        for (int o = 4;; o++) {
            const bool gt = (unsigned)(o - GATE_O) < 2u;
            STEP2(2, o & 1, 4 * o + 2);
            if (RS == 4 && o == 10) break;
            if (o == 4 && wt == 0) mbar_arrive(BAR(B_SPF));
            if (gt) GATE(0);
            STEP2(3, o & 1, 4 * o + 3);
            if (RS == 7 && o == 9) break;
            if (gt) GATE(4);
            STEP2(0, ~o & 1, 4 * o + 4);
            if (RS == 6 && o == 9) break;
            if (gt) GATE(8);
            STEP2(1, ~o & 1, 4 * o + 5);
            if (RS == 5 && o == 9) break;
            if (gt) GATE(12);
        }
#undef P4OK
#define P4OK 1
#define HSTEP(h) MMA_H(0, ha_off(h), hb_off(h))
        mbar_wait(BAR(B_SEL), 0);
        const uint32_t tag = __shfl_sync(0xffffffffu, *reinterpret_cast<volatile unsigned*>(smem + OFF_SEL + 12) & 1, 0);
        uint4* xdst = P.scr->xch + (size_t)(b ^ 16) * 2048 + tid_now();
        asm volatile("" : "+l"(xdst));
        __uint128_t sv[8];
#define SENT(tab, p) ((p) > 12 ? 8 : (int)((((unsigned long long)(tab) | 0x888888888888ull << (4 * SNDN)) << 4 >> (4 * (p))) & 15))
#define SEND(p) do { _Pragma("unroll") for (int v = 0; v < 8; v++) { \
            const bool s0 = v >= SENT(SND0, p) && v < SENT(SND0, (p) + 1), s1 = v >= SENT(SND1, p) && v < SENT(SND1, (p) + 1); \
            if ((wg ? s1 : s0) && (!(NOXCH & 1) || blockIdx.y)) st_relaxed128(xdst + v * 256, sv[v]); } } while (0)
        WAIT_FULL(hs(3), hp(3) ^ 1, 47 - RS);
        MMA_H(64, hs(3) * STAGE_BYTES, b2_off(hs(3)) + 16384);
        wg_wait<1>(); RELEASE(hs(2));
        MMA_H(0, hs(3) * STAGE_BYTES, b2_off(hs(3)));
        mbar_wait(BAR(hf_bar(0)), hf_par(0));
        HSTEP(0);
        wg_wait<2>();
        fence_regs64<64>(ac2);
        TRACE_C(56);
#pragma unroll
        for (int v = 0; v < 8; v++) {
            const int k = 64 + 16 * (v >> 1) + 2 * (v & 1);
            sv[v] = make128((pack_bf(ac2[k], ac2[k + 1]) & ~1u) | tag, pack_bf(ac2[k + 4], ac2[k + 5]), pack_bf(ac2[k + 8], ac2[k + 9]), pack_bf(ac2[k + 12], ac2[k + 13]));
        }
        SEND(0);
        wg_wait<1>(); RELEASE(hs(3));
        uint4 rv[8];
        const uint4* const xsrc = xdst + (part ? 16 * 2048 : -16 * 2048);
        unsigned probe = tag;
#define FETCH_RV() do { _Pragma("unroll") for (int v = 0; v < 8; v++) rv[v] = ld_relaxed128(xsrc + v * 256); } while (0)
#define PROBE() probe = ld_relaxed(&xsrc[7 * 256 + 31 - (tid_now() & 31)].x)
#define AFTER(h) do { if (!(NOXCH & 2)) { \
            if (PRB == PRB1 ? NH - PRB == (h) : NH - PRB == (h) ? wg == 0 : NH - PRB1 == (h) && wg == 1) PROBE(); \
            if (RCV == RCV1 ? NH - RCV == (h) : NH - RCV == (h) ? wg == 0 : NH - RCV1 == (h) && wg == 1) ONCE(if (!((probe ^ tag) & 1)) FETCH_RV();); } \
            if (STG && NH - 9 + STG == (h) && wg == 1) named_bar<8, 256>(); } while (0)
#define HALF(h) do { mbar_wait(BAR(hf_bar(h)), hf_par(h)); TRACE_C((h) + 7 >= NH ? 44 + 7 + (h) - NH : 63); HSTEP(h); SEND(h); \
            if ((h) + 6 < NH || (h) - 1 == DEADH) { wg_wait<1>(); RELEASE(he_bar((h) - 1) - B_EMPTY); } } while (0)
#define HALF_A(h) do { if ((h) < NH && (h) <= SNDN) HALF(h); } while (0)
#define HALF_B(h) do { if ((h) < NH && (h) > SNDN) { HALF(h); AFTER(h); } } while (0)
        HALF_A(1); HALF_A(2); HALF_A(3); HALF_A(4); HALF_A(5); HALF_A(6); HALF_A(7); HALF_A(8);
        TRACE_C(57);
#pragma unroll
        for (int v = 0; v < 8; v++) rv[v] = make_uint4((NOXCH & 2) ? tag : ~tag, 0, 0, 0);
        AFTER(SNDN);
        HALF_B(1); HALF_B(2); HALF_B(3); HALF_B(4); HALF_B(5); HALF_B(6); HALF_B(7); HALF_B(8); HALF_B(9); HALF_B(10); HALF_B(11); HALF_B(12); HALF_B(13);
        if (STG && wg == 0) named_arrive<8, 256>();
        TRACE_C(58);
        const int t2 = tid_now();
        __nv_bfloat16* op = P.out + (size_t)(j * 128 + (t2 >> 5) * 16 + ((t2 >> 2) & 7)) * D_ + eb * 256 + part * 128 + (t2 & 3) * 8;
        asm volatile("" : "+l"(op));
        const int sl = 0xffff - (int)(*reinterpret_cast<volatile unsigned*>(smem + OFF_SEL) & 0xffffu) - j * 128 - (t2 >> 5) * 16;
        const bool lo = ((t2 >> 2) & 7) == sl, hi = ((t2 >> 2) & 7) + 8 == sl;
        if ((unsigned)sl < 16u) {
            mbar_wait(BAR(he_bar(DEADH)), he_par(DEADH));
#pragma unroll
            for (int i = 0; i < 32; i++) if ((i & 4) ? hi : lo) { g[i] = 0x3f803f80u; xr[i] = 0; }
        }
        while (true) {
            uint32_t bad = 0;
#pragma unroll
            for (int v = 0; v < 8; v++) bad |= rv[v].x ^ tag;
            if (__all_sync(0xffffffffu, !(bad & 1)) || !IN_TIME()) break;
            if ((t2 & 31) == 31) { while (((ld_relaxed(&xsrc[7 * 256].x) ^ tag) & 1) && IN_TIME()) {} }
            __syncwarp();
#pragma unroll
            for (int v = 0; v < 8; v++) rv[v] = ld_relaxed128(xsrc + v * 256);
        }
        TRACE_C(59);
        ONCE(_Pragma("unroll") for (int v = 0; v < 8; v++) {
            const int i = 4 * v;
            xr[i] = bfma2(rv[v].x & ~1u, g[i], xr[i]); xr[i + 1] = bfma2(rv[v].y, g[i + 1], xr[i + 1]);
            xr[i + 2] = bfma2(rv[v].z, g[i + 2], xr[i + 2]); xr[i + 3] = bfma2(rv[v].w, g[i + 3], xr[i + 3]);
        });
        wg_wait<0>();
        fence_regs64<0>(ac2);
        TRACE_C(60);
#pragma unroll
        for (int n = 0; n < 8; n += 2) {
            uint32_t o[8];
#pragma unroll
            for (int e = 0; e < 8; e++) {
                const int h = n >> 2, a = (n & 3) + (e >> 2), k = 16 * a + 2 * h + 4 * (e & 3), i = 8 * a + 4 * h + (e & 3);
                o[e] = bfma2(pack_bf(ac2[k], ac2[k + 1]), g[i], xr[i]);
            }
            ONCE(if ((n >> 2) ? hi : lo) {
                     sts128(sb + OFF_SROW + (n & 3) * 64 + (t2 & 3) * 16, o[0], o[1], o[2], o[3]);
                     sts128(sb + OFF_SROW + (n & 3) * 64 + 64 + (t2 & 3) * 16, o[4], o[5], o[6], o[7]);
                 } else {
                     stg128(op + (n >> 2) * 8 * D_ + (n & 3) * 32, o[0], o[1], o[2], o[3]);
                     stg128(op + (n >> 2) * 8 * D_ + (n & 3) * 32 + 32, o[4], o[5], o[6], o[7]);
                 });
        }
        if ((unsigned)sl < 16u) { __syncwarp(); if ((t2 & 31) == 0) mbar_arrive(BAR(B_UPD)); }
    }
}

typedef CUresult (*EncodeFn)(CUtensorMap*, CUtensorMapDataType, cuuint32_t, void*, const cuuint64_t*, const cuuint64_t*,
                             const cuuint32_t*, const cuuint32_t*, CUtensorMapInterleave, CUtensorMapSwizzle,
                             CUtensorMapL2promotion, CUtensorMapFloatOOBfill);

void make_map(EncodeFn fn, CUtensorMap* tm, const void* p, uint64_t rows, uint64_t cols) {
    cuuint64_t dims[2] = {cols, rows};
    cuuint64_t strides[1] = {cols * 2};
    cuuint32_t box[2] = {64, 128};
    cuuint32_t es[2] = {1, 1};
    fn(tm, CU_TENSOR_MAP_DATA_TYPE_BFLOAT16, 2, const_cast<void*>(p), dims, strides, box, es, CU_TENSOR_MAP_INTERLEAVE_NONE,
       CU_TENSOR_MAP_SWIZZLE_128B, CU_TENSOR_MAP_L2_PROMOTION_L2_128B, CU_TENSOR_MAP_FLOAT_OOB_FILL_NONE);
}

}

extern "C" void kernel_launch(void* const* d_in, const int* in_sizes, int n_in, void* d_out, int out_size) {
    (void)in_sizes; (void)n_in; (void)out_size;
    static EncodeFn fn = nullptr;
    static void* scr = nullptr;
    if (!fn) {
        void* p = nullptr;
        cudaDriverEntryPointQueryResult q;
        cudaGetDriverEntryPoint("cuTensorMapEncodeTiled", &p, cudaEnableDefault, &q);
        fn = (EncodeFn)p;
        cudaGetSymbolAddress(&scr, g_scr);
        cudaFuncSetAttribute(fnet_fused_kernel, cudaFuncAttributeMaxDynamicSharedMemorySize, SMEM_BYTES);
    }
    CUtensorMap tx, tdre, tdim, tcre, tcim;
    make_map(fn, &tx, d_in[0], S_, D_);
    make_map(fn, &tcre, d_in[1], S_, S_);
    make_map(fn, &tcim, d_in[2], S_, S_);
    make_map(fn, &tdre, d_in[3], D_, D_);
    make_map(fn, &tdim, d_in[4], D_, D_);
    Params P;
    P.x = (const __nv_bfloat16*)d_in[0];
    P.dre = (const __nv_bfloat16*)d_in[3];
    P.dim = (const __nv_bfloat16*)d_in[4];
    P.cre = (const __nv_bfloat16*)d_in[1];
    P.cim = (const __nv_bfloat16*)d_in[2];
    P.wr = (const __nv_bfloat16*)d_in[6];
    P.wg = (const __nv_bfloat16*)d_in[7];
    P.wu = (const __nv_bfloat16*)d_in[8];
    P.wd = (const __nv_bfloat16*)d_in[9];
    P.out = (__nv_bfloat16*)d_out;
    P.scr = (Scratch*)scr;
    fnet_fused_kernel<<<NCTA + 4, NTHREADS, SMEM_BYTES, cudaStreamPerThread>>>(tx, tdre, tdim, tcre, tcim, P);
}
```

```cpp
#include <cuda_runtime.h>
#include <cuda_bf16.h>
#include <cuda.h>
#include <stdint.h>

#define PACE1 450
#define PACE2 1400
#define PACE3 2300
#define D0 4000
#define DGAP 800
#define DLAG 2
#define XPD 500
#define XPT 8400
#define BPT 12000
#define RSD 11000
#define GUS 29
#define CPN 4
#define GR 7
#define I0 0
#define SPW 5
#define SPG 700
#define DELAY0 2000
#define DELAY2 6000
#define SPACE0 1000
#define FRS 49
#define WS0 22
#define WS1 31
#define WS2 (42 - RS)
#define WS3 (45 - RS)
#define MSL 200
#define GATE_O 4
#define SNDN 7
#define SND0 0x8765432
#define SND1 0x7654321
#define STG 5
#define PRB 5
#define RCV 4
#define POLL1 2
#define PRB1 PRB
#define RCV1 RCV
#define FRSH 3
#define SLEEP_NS 80
#define GOD 900
#define WSL 40
#define BSP0 80
#define BSP1 110

#define RS 7
#define PROD_REGS 32
#define HELP_REGS 64
#define CONS_REGS 208
#define NB 8

namespace {

constexpr int S_ = 2048, D_ = 1024, F_ = 3584;
constexpr int NCTA = 128;
constexpr int OWN = GR * 128, SLR = (D_ - OWN) / 4;
constexpr int NMOE = 112;
constexpr uint32_t A_BYTES = 16384, B_BYTES = 32768, STAGE_BYTES = A_BYTES + B_BYTES;
constexpr uint32_t OFF_X = 4 * STAGE_BYTES;
constexpr uint32_t OFF_MO = OFF_X + 24576;
constexpr uint32_t OFF_SP = STAGE_BYTES + A_BYTES;
constexpr uint32_t OFF_BAR = OFF_X + 32768;
constexpr uint32_t OFF_XN = OFF_BAR + 304;
constexpr uint32_t OFF_RED = OFF_XN + 2112;
constexpr uint32_t OFF_H = OFF_RED + 512;
constexpr uint32_t OFF_SEL = OFF_H + 128;
constexpr uint32_t SMEM_BYTES = OFF_SEL + 16;
constexpr uint32_t SB0 = 1024;
constexpr int NTHREADS = 512;
static_assert(SMEM_BYTES <= 232448, "smem");
__host__ __device__ constexpr uint32_t b2_off(int s) { return s == 1 ? OFF_X : (s == 0 ? 3 : s == 2 ? 0 : 2) * STAGE_BYTES + A_BYTES; }
__host__ __device__ constexpr int hs(int i) { return (i + 4 - RS) & 3; }
__host__ __device__ constexpr int hp(int i) { return ((48 - RS + i) >> 2) & 1; }
constexpr int NH = 2 * RS;
constexpr int DEADH = NH - 7;
__host__ __device__ constexpr uint32_t ha_off(int h) {
    return h % 7 == 0 ? OFF_SP : h % 7 == 1 ? OFF_SP + 16384 : h % 7 == 6 ? b2_off(hs(3)) + 16384 : hs(h % 7 - 2) * STAGE_BYTES;
}
__host__ __device__ constexpr uint32_t hb_off(int h) { return b2_off(hs((h % 7) >> 1)) + (h % 7 & 1) * 16384; }

enum {
    B_FULL = 0, B_EMPTY = 4,
    B_EPI = 8,
    B_HRD = 12,
    B_DR = 17,
    B_RSD = 21,
    B_STATS,
    B_W1M, B_W0D,
    B_HS,
    B_SPF,
    B_HX,
    B_SEL = B_HX + 3, B_GU, B_PEER, B_PR2, B_FIN, B_UPD,
    B_COUNT
};
__host__ __device__ constexpr int hf_bar(int h) { return h % 7 == 1 ? B_HX : h % 7 == 3 ? B_HX + 1 : h % 7 == 6 ? B_HX + 2 : B_FULL + hs(h % 7 == 5 ? 3 : (h % 7) >> 1); }
__host__ __device__ constexpr int hf_par(int h) { return (h % 7 == 1 || h % 7 == 3 || h % 7 == 6 ? 0 : hp(h % 7 == 5 ? 3 : (h % 7) >> 1)) ^ (h / 7); }
__host__ __device__ constexpr int he_bar(int h) { return h < 2 ? B_EMPTY + hs(h) : h < 6 ? B_EPI + h - 2 : B_EMPTY + hs(h - 4); }
__host__ __device__ constexpr int he_par(int h) { return h < 2 ? hp(h) : h < 6 ? 1 : hp(h - 4); }
constexpr uint32_t OFF_PARK = ha_off(DEADH);
constexpr uint32_t OFF_SROW = OFF_PARK + 6144;
__host__ __device__ constexpr uint32_t bar_count(int i) {
    return i < B_EMPTY ? 1 : i < B_HRD || i == B_W1M ? 4 : i < B_DR ? 12 : i <= B_RSD || i == B_SPF ? 3 : i == B_STATS ? 5 : 1;
}
constexpr uint32_t OFF_MIR = OFF_BAR + 288;
static_assert(8 * B_COUNT <= 288 && OFF_MIR + 16 <= OFF_XN, "barriers");

struct Scratch {
    uint4 part[2 * (NMOE / 2) * (D_ / 4)];
    uint4 xp[4 * S_];
    uint2 rs[2 * D_];
    uint4 best[2 * NCTA];
    uint4 gu[4 * F_];
    unsigned long long abflag[8 * 16];
    unsigned epoch[NCTA];
    uint4 epoch2[4];
    alignas(1024) uint4 xch[NCTA * 2048];
    uint8_t ab[8u * 32u * 32768u];
};
__device__ __align__(1024) Scratch g_scr;
#define TRACE(i) do {} while (0)
#define TRACE_C(i) do {} while (0)
#define TRACE_G(i) do {} while (0)

__device__ __forceinline__ uint32_t smem_u32(const void* p) { return (uint32_t)__cvta_generic_to_shared(p); }
__device__ __forceinline__ void mbar_init(uint32_t bar, uint32_t cnt) {
    asm volatile("mbarrier.init.shared::cta.b64 [%0], %1;" ::"r"(bar), "r"(cnt) : "memory");
}
__device__ __forceinline__ unsigned clk_hi() { unsigned t; asm volatile("mov.u32 %0, %%clock_hi;" : "=r"(t)); return t; }
#define MBAR_WAIT_(name, sem, idle) \
__device__ __forceinline__ void name(uint32_t bar, uint32_t parity, unsigned dl) { \
    asm volatile("{\n.reg .pred p;\n.reg .b32 t;\nL:\nmbarrier.try_wait.parity" sem ".shared::cta.b64 p, [%0], %1;\n@p bra D;\n" idle \
                 "mov.u32 t, %%clock_hi;\nsetp.le.u32 p, t, %2;\n@p bra L;\nD:\n}" ::"r"(bar), "r"(parity), "r"(dl), "n"(SLEEP_NS) : "memory"); }
MBAR_WAIT_(mbar_wait_, "", "")
MBAR_WAIT_(mbar_wait_sleep_, "", "nanosleep.u32 %3;\n")
MBAR_WAIT_(mbar_wait_cluster_, ".acquire.cluster", "")
#define mbar_wait(bar, parity) mbar_wait_(bar, parity, dl)
#define mbar_wait_sleep(bar, parity) mbar_wait_sleep_(bar, parity, dl)
#define mbar_wait_cluster(bar, parity) mbar_wait_cluster_(bar, parity, dl)
#define IN_TIME() (clk_hi() <= dl)
__device__ __forceinline__ void st_async2(uint32_t dst, float a, float b, uint32_t bar) {
    asm volatile("st.async.weak.shared::cluster.mbarrier::complete_tx::bytes.v2.f32 [%0], {%1, %2}, [%3];" ::"r"(dst), "f"(a), "f"(b), "r"(bar) : "memory");
}
__device__ __forceinline__ void st_async4(uint32_t dst, float a, float b, float c, float d, uint32_t bar) {
    asm volatile("st.async.weak.shared::cluster.mbarrier::complete_tx::bytes.v4.f32 [%0], {%1, %2, %3, %4}, [%5];"
                 ::"r"(dst), "f"(a), "f"(b), "f"(c), "f"(d), "r"(bar) : "memory");
}
__device__ __forceinline__ void mbar_arrive(uint32_t bar) {
    asm volatile("mbarrier.arrive.shared::cta.b64 _, [%0];" ::"r"(bar) : "memory");
}
__device__ __forceinline__ void mbar_arrive_after(uint32_t bar, uint32_t data) { mbar_arrive(bar + (data & blockIdx.y)); }
__device__ __forceinline__ void mbar_arrive_cluster(uint32_t cluster_bar) {
    asm volatile("mbarrier.arrive.shared::cluster.b64 _, [%0];" ::"r"(cluster_bar) : "memory");
}
__device__ __forceinline__ void mbar_expect_tx(uint32_t bar, uint32_t bytes) {
    asm volatile("mbarrier.arrive.expect_tx.shared::cta.b64 _, [%0], %1;" ::"r"(bar), "r"(bytes) : "memory");
}
__device__ __forceinline__ bool elect_one() {
    uint32_t p;
    asm volatile("{\n.reg .pred p;\nelect.sync _|p, 0xffffffff;\nselp.u32 %0, 1, 0, p;\n}" : "=r"(p));
    return p;
}
__device__ __forceinline__ uint32_t mapa(uint32_t addr, uint32_t rank) {
    uint32_t r;
    asm("mapa.shared::cluster.u32 %0, %1, %2;" : "=r"(r) : "r"(addr), "r"(rank));
    return r;
}
__device__ __forceinline__ void tma_2d(uint32_t dst, const CUtensorMap* tm, int c0, int c1, uint32_t bar) {
    asm volatile("cp.async.bulk.tensor.2d.shared::cluster.global.mbarrier::complete_tx::bytes [%0], [%1, {%3, %4}], [%2];"
                 ::"r"(dst), "l"(tm), "r"(bar), "r"(c0), "r"(c1) : "memory");
}
__device__ __forceinline__ void tma_2d_mc(uint32_t dst, const CUtensorMap* tm, int c0, int c1, uint32_t bar) {
    asm volatile("cp.async.bulk.tensor.2d.shared::cluster.global.mbarrier::complete_tx::bytes.multicast::cluster [%0], [%1, {%3, %4}], [%2], %5;"
                 ::"r"(dst), "l"(tm), "r"(bar), "r"(c0), "r"(c1), "h"((uint16_t)3) : "memory");
}
__device__ __forceinline__ void bulk_g2s_mc(uint32_t dst, const void* src, uint32_t bytes, uint32_t bar) {
    asm volatile("cp.async.bulk.shared::cluster.global.mbarrier::complete_tx::bytes.multicast::cluster [%0], [%1], %2, [%3], %4;"
                 ::"r"(dst), "l"(src), "r"(bytes), "r"(bar), "h"((uint16_t)3) : "memory");
}
__device__ __forceinline__ void bulk_g2s(uint32_t dst, const void* src, uint32_t bytes, uint32_t bar) {
    asm volatile("cp.async.bulk.shared::cluster.global.mbarrier::complete_tx::bytes [%0], [%1], %2, [%3];"
                 ::"r"(dst), "l"(src), "r"(bytes), "r"(bar) : "memory");
}
__device__ __forceinline__ void fence_async_smem() { asm volatile("fence.proxy.async.shared::cta;" ::: "memory"); }
__device__ __forceinline__ void prefetch_tmap(const CUtensorMap* tm) {
    asm volatile("prefetch.tensormap [%0];" ::"l"(tm) : "memory");
}
__device__ __forceinline__ unsigned long long ld_relaxed64(const unsigned long long* p) {
    unsigned long long v; asm volatile("ld.relaxed.gpu.global.u64 %0, [%1];" : "=l"(v) : "l"(p) : "memory"); return v;
}
__device__ __forceinline__ unsigned ld_relaxed8(const uint8_t* p) {
    unsigned v; asm volatile("ld.relaxed.gpu.global.u8 %0, [%1];" : "=r"(v) : "l"(p) : "memory"); return v;
}
__device__ __forceinline__ unsigned load_epoch(const unsigned* p) {
    unsigned v; asm volatile("ld.global.u32 %0, [%1];" : "=r"(v) : "l"(p) : "memory"); return v + 1;
}
__device__ __forceinline__ unsigned ld_relaxed(const unsigned* p) {
    unsigned v; asm volatile("ld.relaxed.gpu.global.u32 %0, [%1];" : "=r"(v) : "l"(p) : "memory"); return v;
}
__device__ __forceinline__ uint4 ld_relaxed128(const uint4* p) {
    uint4 v;
    asm volatile("{\n.reg .b128 t;\n.reg .b64 lo, hi;\nld.relaxed.gpu.global.b128 t, [%4];\nmov.b128 {lo, hi}, t;\n"
                 "mov.b64 {%0, %1}, lo;\nmov.b64 {%2, %3}, hi;\n}"
                 : "=r"(v.x), "=r"(v.y), "=r"(v.z), "=r"(v.w) : "l"(p) : "memory");
    return v;
}
__device__ __forceinline__ void st_relaxed128(uint4* p, const uint4& v) {
    asm volatile("{\n.reg .b128 t;\n.reg .b64 lo, hi;\nmov.b64 lo, {%1, %2};\nmov.b64 hi, {%3, %4};\nmov.b128 t, {lo, hi};\n"
                 "st.relaxed.gpu.global.b128 [%0], t;\n}"
                 ::"l"(p), "r"(v.x), "r"(v.y), "r"(v.z), "r"(v.w) : "memory");
}
__device__ __forceinline__ __uint128_t make128(uint32_t a, uint32_t b, uint32_t c, uint32_t d) {
    __uint128_t v;
    asm volatile("{\n.reg .b64 lo, hi;\nmov.b64 lo, {%1, %2};\nmov.b64 hi, {%3, %4};\nmov.b128 %0, {lo, hi};\n}" : "=q"(v) : "r"(a), "r"(b), "r"(c), "r"(d));
    return v;
}
__device__ __forceinline__ void st_relaxed128(uint4* p, __uint128_t v) {
    asm volatile("st.relaxed.gpu.global.b128 [%0], %1;" ::"l"(p), "q"(v) : "memory");
}
__device__ __forceinline__ void st_relaxed64(uint2* p, uint32_t lo, uint32_t hi) {
    asm volatile("{\n.reg .b64 t;\nmov.b64 t, {%1, %2};\nst.relaxed.gpu.global.b64 [%0], t;\n}" ::"l"(p), "r"(lo), "r"(hi) : "memory");
}
__device__ __forceinline__ void stg128(void* p, uint32_t a, uint32_t b, uint32_t c, uint32_t d) {
    asm volatile("st.global.v4.u32 [%0], {%1,%2,%3,%4};" ::"l"(p), "r"(a), "r"(b), "r"(c), "r"(d) : "memory");
}
__device__ __forceinline__ void sts128(uint32_t p, uint32_t a, uint32_t b, uint32_t c, uint32_t d) {
    asm volatile("st.shared.v4.u32 [%0], {%1,%2,%3,%4};" ::"r"(p), "r"(a), "r"(b), "r"(c), "r"(d) : "memory");
}
__device__ __forceinline__ uint4 lds128(uint32_t p) {
    uint4 v;
    asm volatile("ld.shared.v4.u32 {%0,%1,%2,%3}, [%4];" : "=r"(v.x), "=r"(v.y), "=r"(v.z), "=r"(v.w) : "r"(p) : "memory");
    return v;
}
__device__ __forceinline__ void prefetch_l2(const void* p) { asm volatile("prefetch.global.L2 [%0];" ::"l"(p)); }
__device__ __forceinline__ void st_release8(void* p, unsigned v) {
    asm volatile("st.release.gpu.global.u8 [%0], %1;" ::"l"(p), "r"(v) : "memory");
}
__device__ __forceinline__ uint64_t policy_evict_first() {
    uint64_t pol;
    asm("createpolicy.fractional.L2::evict_first.b64 %0, 1.0;" : "=l"(pol));
    return pol;
}
__device__ __forceinline__ uint4 ldg_stream(const void* p, uint64_t pol) {
    uint4 v;
    asm volatile("ld.global.nc.L1::no_allocate.L2::cache_hint.v4.u32 {%0,%1,%2,%3}, [%4], %5;"
                 : "=r"(v.x), "=r"(v.y), "=r"(v.z), "=r"(v.w) : "l"(p), "l"(pol));
    return v;
}
__device__ __forceinline__ void ldg_stream_next(uint4& v, const char*& p, uint32_t stride, uint64_t pol) {
    asm volatile("{\n.reg .pred q;\nsetp.ne.u32 q, %5, 0;\n"
                 "@q ld.global.nc.L1::no_allocate.L2::cache_hint.v4.u32 {%0,%1,%2,%3}, [%4], %6;\nmad.wide.u32 %4, %5, 1, %4;\n}"
                 : "+r"(v.x), "+r"(v.y), "+r"(v.z), "+r"(v.w), "+l"(p) : "r"(stride), "l"(pol));
}
template <int ID, int N> __device__ __forceinline__ void named_arrive() { asm volatile("bar.arrive %0, %1;" ::"n"(ID), "n"(N) : "memory"); }
template <int ID, int N> __device__ __forceinline__ void named_bar() { asm volatile("bar.sync %0, %1;" ::"n"(ID), "n"(N) : "memory"); }

__device__ __forceinline__ float bf_lo(uint32_t u) { return __uint_as_float(u << 16); }
__device__ __forceinline__ float bf_hi(uint32_t u) { return __uint_as_float(u & 0xffff0000u); }
__device__ __forceinline__ uint32_t pack_bf(float lo, float hi) {
    uint32_t r; asm("cvt.rn.bf16x2.f32 %0, %1, %2;" : "=r"(r) : "f"(hi), "f"(lo)); return r;
}
__device__ __forceinline__ float rbf(float v) { return __uint_as_float(pack_bf(0.f, v)); }
__device__ __forceinline__ float silu_f(float z) { return __fdividef(z, 1.0f + __expf(-z)); }
__device__ __forceinline__ uint32_t bfma2(uint32_t a, uint32_t b, uint32_t c) {
    uint32_t r; asm("fma.rn.bf16x2 %0, %1, %2, %3;" : "=r"(r) : "r"(a), "r"(b), "r"(c)); return r;
}
__device__ __forceinline__ uint32_t norm2(uint32_t xv, float m, float rinv) {
    uint32_t t = pack_bf(bf_lo(xv) - m, bf_hi(xv) - m);
    return pack_bf(bf_lo(t) * rinv, bf_hi(t) * rinv);
}
__device__ __forceinline__ float gate1(float x, float rinv, float mr) {
    const float h = fmaf(x, 0.5f * rinv, 0.5f * mr);
    float t;
    asm("tanh.approx.f32 %0, %1;" : "=f"(t) : "f"(h));
    return fmaf(h, t, h);
}
__device__ __forceinline__ uint32_t gate2(uint32_t xv, float rinv, float mr) {
    return pack_bf(gate1(bf_lo(xv), rinv, mr), gate1(bf_hi(xv), rinv, mr));
}
__device__ __forceinline__ uint32_t silu2(uint32_t z) { return pack_bf(silu_f(bf_lo(z)), silu_f(bf_hi(z))); }

__device__ __forceinline__ void wg_fence() { asm volatile("wgmma.fence.sync.aligned;" ::: "memory"); }
__device__ __forceinline__ void wg_commit() { asm volatile("wgmma.commit_group.sync.aligned;" ::: "memory"); }
template <int N> __device__ __forceinline__ void wg_wait() { asm volatile("wgmma.wait_group.sync.aligned %0;" ::"n"(N) : "memory"); }

__host__ __device__ constexpr uint32_t desc_lo(uint32_t addr, uint32_t lbo) { return ((addr & 0x3FFFF) >> 4) | ((lbo >> 4) << 16); }

#define R8(a, o) "+f"(a[(o) + 0]), "+f"(a[(o) + 1]), "+f"(a[(o) + 2]), "+f"(a[(o) + 3]), \
                 "+f"(a[(o) + 4]), "+f"(a[(o) + 5]), "+f"(a[(o) + 6]), "+f"(a[(o) + 7])
#define R64(a, o) R8(a, (o) + 0), R8(a, (o) + 8), R8(a, (o) + 16), R8(a, (o) + 24), \
                  R8(a, (o) + 32), R8(a, (o) + 40), R8(a, (o) + 48), R8(a, (o) + 56)

template <int O, int TB = 1>
__device__ __forceinline__ void wgmma128(float (&a)[128], uint32_t da, uint32_t db, int scale_d) {
    asm volatile(
        "{\n.reg .pred p;\n.reg .b64 da, db;\nsetp.ne.b32 p, %66, 0;\n"
        "mov.b64 da, {%64, 0x40000040};\nmov.b64 db, {%65, %68};\n"
        "wgmma.mma_async.sync.aligned.m64n128k16.f32.bf16.bf16 "
        "{%0,%1,%2,%3,%4,%5,%6,%7,%8,%9,%10,%11,%12,%13,%14,%15,"
        "%16,%17,%18,%19,%20,%21,%22,%23,%24,%25,%26,%27,%28,%29,%30,%31,"
        "%32,%33,%34,%35,%36,%37,%38,%39,%40,%41,%42,%43,%44,%45,%46,%47,"
        "%48,%49,%50,%51,%52,%53,%54,%55,%56,%57,%58,%59,%60,%61,%62,%63},"
        "da, db, p, 1, 1, 0, %67;\n}"
        : R64(a, O)
        : "r"(da), "r"(db), "r"(scale_d), "n"(TB), "n"(TB ? 0x80000020 : 0x40000040));
}
template <int O>
__device__ __forceinline__ void wgmma128_k8(float (&a)[128], uint32_t da, uint32_t db) {
    asm volatile(
        "{\n.reg .b64 da, db;\nmov.b64 da, {%64, 8};\nmov.b64 db, {%65, 8};\n"
        "wgmma.mma_async.sync.aligned.m64n128k16.f32.bf16.bf16 "
        "{%0,%1,%2,%3,%4,%5,%6,%7,%8,%9,%10,%11,%12,%13,%14,%15,"
        "%16,%17,%18,%19,%20,%21,%22,%23,%24,%25,%26,%27,%28,%29,%30,%31,"
        "%32,%33,%34,%35,%36,%37,%38,%39,%40,%41,%42,%43,%44,%45,%46,%47,"
        "%48,%49,%50,%51,%52,%53,%54,%55,%56,%57,%58,%59,%60,%61,%62,%63},"
        "da, db, 1, 1, 1, 0, 0;\n}"
        : R64(a, O)
        : "r"(da), "r"(db));
}
template <int O>
__device__ __forceinline__ void fence_regs64(float (&a)[128]) {
    asm volatile("" : R64(a, O)::"memory");
}

struct Params {
    const __nv_bfloat16* x;
    const __nv_bfloat16* dre;
    const __nv_bfloat16* dim;
    const __nv_bfloat16* cre;
    const __nv_bfloat16* cim;
    const __nv_bfloat16* wr;
    const __nv_bfloat16* wg;
    const __nv_bfloat16* wu;
    const __nv_bfloat16* wd;
    __nv_bfloat16* out;
    Scratch* scr;
};

__device__ __forceinline__ float warp_sum(float v) {
#pragma unroll
    for (int o = 16; o; o >>= 1) v += __shfl_xor_sync(0xffffffffu, v, o);
    return v;
}
__device__ __forceinline__ float sum8(const uint4& v) {
    return ((bf_lo(v.x) + bf_hi(v.x)) + (bf_lo(v.y) + bf_hi(v.y))) + ((bf_lo(v.z) + bf_hi(v.z)) + (bf_lo(v.w) + bf_hi(v.w)));
}
__device__ __forceinline__ void fma8(float* acc, const uint4& w, float s) {
    acc[0] = fmaf(s, bf_lo(w.x), acc[0]); acc[1] = fmaf(s, bf_hi(w.x), acc[1]); acc[2] = fmaf(s, bf_lo(w.y), acc[2]); acc[3] = fmaf(s, bf_hi(w.y), acc[3]);
    acc[4] = fmaf(s, bf_lo(w.z), acc[4]); acc[5] = fmaf(s, bf_hi(w.z), acc[5]); acc[6] = fmaf(s, bf_lo(w.w), acc[6]); acc[7] = fmaf(s, bf_hi(w.w), acc[7]);
}
__device__ __forceinline__ int tid_now() { int t; asm volatile("mov.u32 %0, %%tid.x;" : "=r"(t)); return t; }

#define GAP(...) do { asm volatile("" : __VA_ARGS__); \
    asm volatile("{\n.reg .pred p;\n.reg .b32 t;\nL: mov.u32 t, %clock_hi;\nsetp.eq.u32 p, t, 0xffffffff;\n@p bra L;\n}"); } while (0)
#define ONCE(...) do { int z_ = one; _Pragma("unroll 1") do { __VA_ARGS__ } while (--z_); } while (0)
__device__ __forceinline__ unsigned clk() { unsigned t; asm volatile("mov.u32 %0, %%clock;" : "=r"(t)); return t; }
__device__ __forceinline__ unsigned keep(unsigned t) { return __shfl_sync(0xffffffffu, t + (threadIdx.x & 31), 0); }
__device__ __forceinline__ void wait_until(unsigned t) { while ((int)(clk() - t) < 0) { if (WSL) __nanosleep(WSL); } }

__device__ __forceinline__ void spare_cta(const Params& P, uint8_t* smem, uint32_t sb, int tid, int warp, int b) {
    const unsigned dl = keep(clk_hi() + 1);
    const unsigned t_in = keep(clk());
    unsigned t0 = t_in + I0;
    const int lane = tid & 31, e = b - NCTA;
    const unsigned ep = load_epoch(&P.scr->epoch2[e].x);
    const char* dsrc = reinterpret_cast<const char*>(((e >> 1) ? P.dim : P.dre) + (size_t)((e & 1) * 512 + (warp & 1) * 32 + 12) * D_);
    const char* wsrc = reinterpret_cast<const char*>(((warp & 1) ? P.wu : P.wg) + (size_t)(OWN + e * SLR) * F_);
    const uint64_t pol = policy_evict_first();
    const uint32_t bar = sb + 15872;
    constexpr int last = 8 + SLR / 2;
    float* xn = reinterpret_cast<float*>(smem);
    float* rsum = reinterpret_cast<float*>(smem + 15360);
    if (tid == 0) { for (int i = 0; i < SPW; i++) mbar_init(bar + 8 * i, 1); fence_async_smem(); }
    float ag[16];
#pragma unroll
    for (int i = 0; i < 16; i++) ag[i] = 0.f;
    int slot = 0, ph = 1;
#pragma unroll 1
    for (int n = -SPW; n < last; n++) {
        const uint32_t st = sb + 16384 + slot * 32768;
        if (n == 8) {
            if (warp == 15) {
                uint4 f;
                wait_until(t_in + BPT + 800);
                while (true) {
                    f = ld_relaxed128(&P.scr->best[2 * (e * 32 + (lane & 15))]);
                    if (__all_sync(0xffffffffu, f.w == ep) || !IN_TIME()) break;
                    __nanosleep(100);
                }
                const unsigned key = __reduce_max_sync(0xffffffffu, f.x);
                const int from = __ffs(__ballot_sync(0xffffffffu, f.x == key)) - 1;
                const float m = __uint_as_float(__shfl_sync(0xffffffffu, f.y, from)), ri = __uint_as_float(__shfl_sync(0xffffffffu, f.z, from));
                const uint32_t n0 = norm2(__ldg(reinterpret_cast<const uint32_t*>(P.x + (size_t)(0xffff - (int)(key & 0xffffu)) * D_ + OWN + e * SLR) + (lane & (SLR / 2 - 1))), m, ri);
                *reinterpret_cast<float2*>(xn + lane * 2) = make_float2(bf_lo(n0), bf_hi(n0));
            }
            __syncthreads();
            t0 = clk();
        }
        if (n >= 0) {
            mbar_wait(bar + 8 * slot, ph);
            if (n < 8) {
                float a0 = 0.f;
#pragma unroll 1
                for (int i = 0; i < 4; i++) a0 += sum8(lds128(st + warp * 2048 + i * 512 + lane * 16));
                a0 = warp_sum(a0);
                if (lane == 0) rsum[n * 16 + warp] = a0;
            } else if (warp < 14) {
                const float2 x2 = *reinterpret_cast<const float2*>(xn + (n - 8) * 2);
#pragma unroll
                for (int i = 0; i < 4; i++) fma8(ag + 8 * (i >> 1), lds128(st + i * 7168 + tid * 16), (i & 1) ? x2.y : x2.x);
            }
        }
        __syncthreads();
        if ((unsigned)n < 8 && tid < 16)
            st_relaxed64(&P.scr->rs[(e >> 1) * D_ + (e & 1) * 512 + (n * 4 + (tid >> 2)) * 16 + 12 + (tid & 3)], __float_as_uint(rsum[n * 16 + tid]), ep);
        const int m = n + SPW;
        if (m < last && warp >= 14) {
            while ((int)(clk() - t0) < 0) {}
            t0 += SPG;
            if (elect_one()) {
                if (warp == 14) mbar_expect_tx(bar + 8 * slot, m < 8 ? 32768 : 28672);
                if (m < 8) {
                    bulk_g2s(st + (warp & 1) * 16384, dsrc + (size_t)m * 64 * 2 * D_, 8192, bar + 8 * slot);
                    bulk_g2s(st + (warp & 1) * 16384 + 8192, dsrc + (size_t)(m * 64 + 16) * 2 * D_, 8192, bar + 8 * slot);
                } else {
                    asm volatile("cp.async.bulk.shared::cluster.global.mbarrier::complete_tx::bytes.L2::cache_hint [%0], [%1], %2, [%3], %4;"
                                 ::"r"(st + (warp & 1) * 14336), "l"(wsrc + (size_t)(m - 8) * 4 * F_), "r"(14336), "r"(bar + 8 * slot), "l"(pol) : "memory");
                }
            }
            __syncwarp();
        }
        if (++slot == SPW) { slot = 0; ph ^= 1; }
    }
    if (warp < 14) {
        float4* ps = reinterpret_cast<float4*>(smem + 16384) + tid * 2;
#pragma unroll
        for (int i = 0; i < 4; i++) ps[(i >> 1) * (F_ / 4) + (i & 1)] = make_float4(ag[4 * i], ag[4 * i + 1], ag[4 * i + 2], ag[4 * i + 3]);
    }
    __syncthreads();
    const uint32_t* ps = reinterpret_cast<const uint32_t*>(smem + 16384);
#pragma unroll 1
    for (int f = tid; f < F_; f += NTHREADS) st_relaxed128(&P.scr->gu[e * F_ + f], make_uint4(ps[f], ps[F_ + f], ep, 0));
    if (tid == 0) P.scr->epoch2[e].x = ep;
}

template <bool BY_SM>
__global__ void __cluster_dims__(2, 1, 1) __launch_bounds__(NTHREADS, 1)
fnet_fused_kernel(const __grid_constant__ CUtensorMap tm_x, const __grid_constant__ CUtensorMap tm_dre,
                  const __grid_constant__ CUtensorMap tm_dim, const __grid_constant__ CUtensorMap tm_cre,
                  const __grid_constant__ CUtensorMap tm_cim, const Params P) {
    extern __shared__ __align__(1024) uint8_t smem_[];
    const int tid = threadIdx.x, lane = tid & 31;
    const int c = blockIdx.x & 1;
    int b = blockIdx.x;
    if (BY_SM) {
        unsigned sm; asm volatile("mov.u32 %0, %%smid;" : "=r"(sm));
        const int t = sm >> 1;
        const int u = t - 32;
        const int pr = u < 0 ? t : u < 28 ? t + 1 + ((u * 37) >> 8) : u < 30 ? t + 4 : (t - 58) * 8;
        b = pr * 2 + c;
    }
    const uint32_t sb = SB0 | (c << 24);
    uint8_t* const smem = reinterpret_cast<uint8_t*>(__cvta_shared_to_generic(sb));
    const int grp = b >> 4;
    const int part = grp & 1;
    const int eb = grp >> 1;
    const int j = b & 15;
    const int sh = eb != 0;
    const int ci = b >> 1;
    const bool moe = b < NMOE;
#define KBLK(it) ((it) <= 4 ? (4 * eb - sh + (it)) ^ sh : 4 * eb - sh + (it) - (4 * eb - sh + (it) > 15 ? 15 : 0))
    const uint32_t bar0 = sb + OFF_BAR;
#define BAR(i) (bar0 + 8u * (i))
#define CLUSTER_ARRIVE() asm volatile("barrier.cluster.arrive.relaxed.aligned;" ::: "memory")
#define CLUSTER_WAIT() asm volatile("barrier.cluster.wait.aligned;" ::: "memory")
#define FENCE_INIT() asm volatile("fence.mbarrier_init.release.cluster;" ::: "memory")
#define TE(i)
    const int warp = __shfl_sync(0xffffffffu, tid >> 5, 0);
    TE(0);
    if (warp == 0 && elect_one()) {
#pragma unroll
        for (int s = 0; s < 4; s++) mbar_init(BAR(B_FULL + s), 1);
        FENCE_INIT();
    }
    __syncwarp();
    CLUSTER_ARRIVE();
    TE(1);
    if (warp == 1 && elect_one()) prefetch_tmap(part ? &tm_dim : &tm_dre);
    const bool first = warp == 0 && b < NCTA;
    if (first && elect_one()) {
        mbar_expect_tx(BAR(B_FULL + 0), STAGE_BYTES);
        tma_2d(sb, &tm_x, 0, j * 128, BAR(B_FULL + 0));
    }
    __syncwarp();
    TE(2);
    CLUSTER_WAIT();
    TE(3);
    if (first && elect_one()) tma_2d_mc(sb + A_BYTES + c * 16384, part ? &tm_dim : &tm_dre, 0, eb * 256 + 128 * (c ^ part), BAR(B_FULL + 0));
    __syncwarp();
    const unsigned t_first = keep(clk());
    if ((warp == 3 || warp == 12) && elect_one()) {
        if (warp != 3) {
#pragma unroll
            for (int s = B_EMPTY; s < 20; s++) mbar_init(BAR(s), bar_count(s));
        } else {
#pragma unroll
            for (int s = 20; s < B_COUNT; s++) mbar_init(BAR(s), bar_count(s));
            *reinterpret_cast<uint4*>(smem + OFF_MIR) = make_uint4(0, 0, 0, 0);
        }
        FENCE_INIT();
    }
    __syncwarp();
    if (warp == 12 && b < NCTA) {
        named_arrive<0, NTHREADS>();
        if (elect_one()) {
            mbar_expect_tx(BAR(B_FULL + 1), STAGE_BYTES);
            while ((int)(clk() - t_first) < PACE1) {}
            tma_2d(sb + STAGE_BYTES, &tm_x, KBLK(1) * 64, j * 128, BAR(B_FULL + 1));
            tma_2d_mc(sb + STAGE_BYTES + A_BYTES + c * 16384, part ? &tm_dim : &tm_dre, KBLK(1) * 64, eb * 256 + 128 * (c ^ part), BAR(B_FULL + 1));
        }
        __syncwarp();
    } else {
        named_bar<0, NTHREADS>();
    }
    if (__popc(smem_u32(smem_) ^ sb) > blockIdx.y) return;
    if (__builtin_expect(b >= NCTA, 0)) { spare_cta(P, smem, sb, tid, warp, b); return; }

    const unsigned dl = keep(clk_hi() + 1);
    if (warp >= 12) {
        asm volatile("setmaxnreg.dec.sync.aligned.u32 %0;" ::"n"(PROD_REGS));
        if (warp == 12) {
            const CUtensorMap* tmD = part ? &tm_dim : &tm_dre;
            const CUtensorMap* tmC = part ? &tm_cim : &tm_cre;
            const int row0 = j * 128, drow = eb * 256 + 128 * (c ^ part), q0 = j >> 1;
            if (elect_one()) {
                const unsigned t0 = t_first;
#pragma unroll 1
                for (int it = 2; it < 16; it++) {
                    const int s = it & 3;
                    const uint32_t st = sb + s * STAGE_BYTES, fb = BAR(B_FULL + s);
                    if (it < 4) {
                        wait_until(t0 + (it == 2 ? PACE2 : PACE3));
                    } else {
                        mbar_wait(BAR(B_EMPTY + s), ((it >> 2) & 1) ^ 1);
                        if (it < 8 + sh) mbar_wait(BAR(B_HRD + it - 4), 0);
                    }
                    mbar_expect_tx(fb, STAGE_BYTES);
                    const int kc = KBLK(it) * 64;
                    tma_2d(st, &tm_x, kc, row0, fb);
                    tma_2d_mc(st + A_BYTES + c * 16384, tmD, kc, drow, fb);
                    TRACE(128 + it);
                    if (it == 4) { prefetch_tmap(&tm_cre); prefetch_tmap(&tm_cim); }
                }
                const unsigned ep = load_epoch(&P.scr->epoch[b]);
#pragma unroll 1
                for (int i = 0; i < 2; i++) {
                    mbar_wait(BAR(B_EMPTY + i), 1);
                    mbar_expect_tx(BAR(B_FULL + i), A_BYTES);
                    tma_2d(sb + i * STAGE_BYTES, tmC, (2 * j + i) * 64, row0, BAR(B_FULL + i));
                    TRACE(128 + 16 + i);
                }
                const uint8_t* abg = P.scr->ab + (size_t)grp * 32 * B_BYTES;
                int it = 18;
                unsigned have = 0;
                auto seen = [&](int word, unsigned want) {
                    if ((have & want) == want) return;
                    do {
                        asm volatile("ld.acquire.cta.shared::cta.u32 %0, [%1];" : "=r"(have) : "r"(sb + OFF_MIR + 4 * word) : "memory");
                    } while ((have & want) != want && IN_TIME());
                    asm volatile("fence.proxy.async.global;" ::: "memory");
                };
                unsigned long long rdy = (unsigned long long)(~ep & 0xffu) * 0x0101010101010101ull;
#pragma unroll 1
                for (int cl = 0; cl < 4; cl++) {
                    const int ko = ((cl & 1) << 1) + (cl >> 1);
#pragma unroll 1
                    for (int n = cl < 2; n < (cl < 3 ? 8 : 8 - RS); n++, it++) {
                        const int q = (q0 + n) & 7, kb = n ? 4 * q + ko : 2 * (j ^ 1) + cl - 2;
                        const int s = it & 3;
                        const uint32_t fb = BAR(B_FULL + s), bs = sb + b2_off(s);
                        if (it != 19) {
                            mbar_wait(BAR(B_EMPTY + s), ((it >> 2) & 1) ^ 1); mbar_expect_tx(fb, STAGE_BYTES);
                            tma_2d(sb + s * STAGE_BYTES, tmC, kb * 64, row0, fb);
                        }
                        if (it == 18) {
                            mbar_wait(BAR(B_EMPTY + 3), 1); mbar_expect_tx(BAR(B_FULL + 3), STAGE_BYTES);
                            tma_2d(sb + 3 * STAGE_BYTES, tmC, ((q + 1) & 7) * 256, row0, BAR(B_FULL + 3));
                        }
                        if (cl == 0) {
                            if (((unsigned)(rdy >> (8 * q)) & 0xffu) != (ep & 0xffu)) {
                                do { rdy = ld_relaxed64(&P.scr->abflag[grp * 16]); } while (((unsigned)(rdy >> (8 * q)) & 0xffu) != (ep & 0xffu) && IN_TIME());
                                asm volatile("fence.acquire.gpu;\nfence.proxy.async.global;" ::: "memory");
                            }
                        } else {
                            seen(0, 1u << (8 * (n ? cl : 2 * cl - 3 - c) + q));
                        }
                        if (it == 18) TRACE(199);
                        if (n) bulk_g2s_mc(bs + c * 16384, abg + (size_t)kb * B_BYTES + c * 16384, 16384, fb);
                        else bulk_g2s(bs, abg + (size_t)kb * B_BYTES, B_BYTES, fb);
                        *reinterpret_cast<volatile int*>(smem + OFF_MIR + 8) = it;
                        TRACE(128 + it);
                    }
                }
                have = 0;
                seen(1, 0xff000000u);
                const uint8_t* abf = P.scr->ab + (size_t)(grp ^ 1) * 32 * B_BYTES + 16384;
                const uint8_t* const ab0 = part ? abf : abg;
                const uint8_t* const ab1 = part ? abg : abf;
                mbar_wait(BAR(B_SPF), 0);
#pragma unroll
                for (int h = 0; h < NH; h++) {
                    const int kb = 4 * ((q0 + 8 - RS + (h >> 1)) & 7) + 3;
                    const uint32_t fb = BAR(hf_bar(h));
                    if (h >= 7) mbar_wait(BAR(he_bar(h - 7)), he_par(h - 7));
                    else if (h != 1 && h != 3 && h != 6) { const int i = h == 5 ? 3 : h >> 1; mbar_wait(BAR(B_EMPTY + hs(i)), hp(i) ^ 1); }
                    mbar_expect_tx(fb, 32768);
                    tma_2d(sb + ha_off(h), (h & 1) ? &tm_cim : &tm_cre, kb * 64, row0, fb);
                    bulk_g2s_mc(sb + hb_off(h) + c * 8192, ((h & 1) ? ab1 : ab0) + (size_t)kb * B_BYTES + c * 8192, 8192, fb);
                    if (h == NH - FRSH) *reinterpret_cast<volatile int*>(smem + OFF_MIR + 8) = FRS;
                    TRACE(128 + 48 - RS + h);
                }
                P.scr->epoch[b] = ep;
            }
        } else {
          const unsigned t_in = t_first;
          const unsigned ep = load_epoch(&P.scr->epoch[b]);
          {
            if (lane == 0) TRACE(227);
#pragma unroll 1
            for (int k = -DLAG; k < 4; k++) {
                const int r = 4 * (warp - 13) + k;
                if (k + DLAG < 4) {
                    wait_until(t_in + D0 + (k + DLAG) * DGAP);
                    if (elect_one()) {
                        mbar_expect_tx(BAR(B_DR + k + DLAG), 2048);
                        bulk_g2s(sb + OFF_X + (r + DLAG) * 2048, (part ? P.dim : P.dre) + (size_t)(eb * 256 + j * 16 + r + DLAG) * D_, 2048, BAR(B_DR + k + DLAG));
                    }
                    __syncwarp();
                }
                if (k < 0) continue;
                mbar_wait_sleep(BAR(B_DR + k), 0);
                if (tid == 13 * 32) TRACE(228 + k);
                uint4 v[4];
#pragma unroll
                for (int i = 0; i < 4; i++) v[i] = lds128(sb + OFF_X + r * 2048 + i * 512 + lane * 16);
                float a0 = 0.f;
#pragma unroll
                for (int i = 0; i < 4; i++) { a0 += sum8(v[i]); if (i & 1) GAP("+f"(a0)); }
                a0 = warp_sum(a0);
                if (lane == 0) reinterpret_cast<float*>(smem + OFF_H)[r] = a0;
            }
#pragma unroll 1
            for (int i = warp - 13; i < CPN; i += 3)
                prefetch_l2((part ? P.cim : P.cre) + (size_t)(j * 128 + eb * 32 + lane) * S_ + (i < 2 ? 2 * j + i : 4 * (((j >> 1) + i - 1) & 7)) * 64);
            if (lane == 0) TRACE(217 + warp - 13);
          }
          if (lane == 0) mbar_arrive(BAR(B_RSD));
          if (warp == 14) {
#define AT_STEP(n) do { while (*reinterpret_cast<volatile int*>(smem + OFF_MIR + 8) < (n) && IN_TIME()) __nanosleep(MSL); } while (0)
#define WATCH(g, word, want) do { const uint8_t* fp = reinterpret_cast<const uint8_t*>(&P.scr->abflag[(g) * 16]) + lane; \
                unsigned known = 0; \
                while (true) { \
                    const unsigned m = __ballot_sync(0xffffffffu, ld_relaxed8(fp) == (ep & 0xffu)); \
                    if (m != known) { \
                        known = m; \
                        asm volatile("fence.acquire.gpu;" ::: "memory"); \
                        __syncwarp(); \
                        if (lane == 0) asm volatile("st.release.cta.shared::cta.u32 [%0], %1;" ::"r"(sb + OFF_MIR + 4 * (word)), "r"(m) : "memory"); \
                    } \
                    if ((m & (want)) == (want) || !IN_TIME()) break; \
                    __nanosleep(MSL); \
                } } while (0)
            AT_STEP(WS0);
            WATCH(grp, 0, 0xffffu);
            if (moe) {
                uint4 g[4];
                const uint4* gp = &P.scr->gu[ci * 64 + c * 32 + lane];
                AT_STEP(GUS);
                while (true) {
                    bool ok = true;
#pragma unroll
                    for (int i = 0; i < 4; i++) { g[i] = ld_relaxed128(gp + i * F_); ok = ok && g[i].z == ep; }
                    if (__all_sync(0xffffffffu, ok) || !IN_TIME()) break;
                    __nanosleep(MSL);
                }
                *reinterpret_cast<float2*>(smem + OFF_RED + lane * 8) =
                    make_float2((__uint_as_float(g[0].x) + __uint_as_float(g[1].x)) + (__uint_as_float(g[2].x) + __uint_as_float(g[3].x)),
                                (__uint_as_float(g[0].y) + __uint_as_float(g[1].y)) + (__uint_as_float(g[2].y) + __uint_as_float(g[3].y)));
                __syncwarp();
                if (lane == 0) { mbar_arrive(BAR(B_GU)); TRACE(223); }
            }
#pragma unroll 1
            for (int k = 0; k < 3; k++) {
                AT_STEP(k == 0 ? WS1 : k == 1 ? WS2 : WS3);
                WATCH(grp ^ (k >> 1), k >> 1, k ? 0xffffffffu : 0xffffffu);
            }
          } else {
           if (warp == 13) {
                uint8_t* dst = smem + OFF_MO;
                mbar_wait(BAR(B_RSD), 0);
                if (lane < 12) st_relaxed64(&P.scr->rs[part * D_ + eb * 256 + j * 16 + lane], reinterpret_cast<const uint32_t*>(smem + OFF_H)[lane], ep);
                wait_until(t_in + RSD);
                if (lane == 0) TRACE(225);
                uint4 f[4];
                bool ok;
#pragma unroll
                for (int i = 0; i < 4; i++) f[i].y = ~ep;
                do {
                    ok = true;
#pragma unroll
                    for (int i = 0; i < 4; i++)
                        if (f[i].y != ep || f[i].w != ep)
                            f[i] = ld_relaxed128(reinterpret_cast<const uint4*>(P.scr->rs) + part * 512 + eb * 128 + 64 * ((i >> 1) ^ part) + (i & 1) * 32 + lane);
#pragma unroll
                    for (int i = 0; i < 4; i++) ok = ok && f[i].y == ep && f[i].w == ep;
                } while (!__all_sync(0xffffffffu, ok) && IN_TIME());
                if (lane == 0) TRACE(226);
#pragma unroll
                for (int i = 0; i < 8; i++) {
                    const float v = 0.5f * __uint_as_float((i & 1) ? f[i >> 1].z : f[i >> 1].x);
                    const float hi = rbf(v), mid = rbf(v - hi), lo = v - hi - mid;
                    *reinterpret_cast<uint4*>(dst + (((i >> 1) * 32 + lane) * 2 + (i & 1)) * 16) = make_uint4(pack_bf(hi, mid), pack_bf(lo, 0.f), 0, 0);
                }
                fence_async_smem();
                __syncwarp();
                if (lane == 0) { mbar_arrive(BAR(B_STATS)); TRACE(204); }
            }
#define FLAG(w) st_release8(reinterpret_cast<uint8_t*>(&P.scr->abflag[grp * 16 + 2 * (w) + c]) + (j >> 1), ep & 0xffu)
            const int hf = (warp >> 1) & 1;
            if (!hf && elect_one()) {
                mbar_wait(BAR(B_EPI), 0);
                mbar_arrive(BAR(B_HS));
                TRACE(206);
                FLAG(0);
                TRACE(207);
            }
            __syncwarp();
            uint8_t* dst = P.scr->ab + (size_t)(grp * 32 + 2 * j + 1) * B_BYTES + hf * 16384 + lane * 16;
            uint32_t src = sb + OFF_SP + hf * 16384 + lane * 16;
            mbar_wait_sleep(BAR(B_EPI + 3), 0);
            unsigned t0 = clk() + (c ? DELAY2 : DELAY0);
#pragma unroll 1
            for (int i = 0; i < 8; i++, src += 2048, dst += 2048, t0 += SPACE0) {
                wait_until(t0);
                uint4 v[4];
#pragma unroll
                for (int u = 0; u < 4; u++) v[u] = lds128(src + u * 512);
#pragma unroll
                for (int u = 0; u < 4; u++) stg128(dst + u * 512, v[u].x, v[u].y, v[u].z, v[u].w);
            }
            named_bar<3, 64>();
            if (!hf && elect_one()) {
                mbar_arrive(BAR(B_SPF));
                TRACE(209);
                FLAG(1);
                TRACE(210);
            }
          }
        }
    } else if (warp >= 8) {
        asm volatile("setmaxnreg.dec.sync.aligned.u32 %0;" ::"n"(HELP_REGS));
        const int aw = warp - 8, mt = tid - 256;
        float* hact = reinterpret_cast<float*>(smem + OFF_H);
        uint4 buf[NB];
#define WP0() reinterpret_cast<const char*>(((aw & 1) ? P.wu : P.wg) + (size_t)(c * (OWN / 2) + (aw >> 1) * (OWN / 4) + ((tid_now() >> 3) & 3)) * F_ + ci * 64 + (tid_now() & 7) * 8)
        {
            const unsigned t_in = t_first;
            const unsigned ep = load_epoch(&P.scr->epoch[b]);
            uint4 w[4];
            w[0] = __ldg(reinterpret_cast<const uint4*>(P.wr + eb * 256 + lane * 8));
            float s1[4], s2[4], sx[4];
#pragma unroll
            for (int r = 0; r < 4; r++) { s1[r] = 0.f; s2[r] = 0.f; sx[r] = 0.f; }
            const int xr0 = part * 64 + aw * 16 + (lane >> 3);
            const uint32_t xa0 = sb + xr0 * 128 + (((lane & 7) ^ (lane >> 3)) << 4);
            if (sh) { mbar_wait_sleep(BAR(B_FULL), 0); if (lane < 3) mbar_arrive(BAR(B_HRD)); }
#pragma unroll 1
            for (int s = sh; s < sh + 4; s++) {
                const int from = ((s - sh) ^ sh) * 8 + (lane & 7);
                const uint4 wn = make_uint4(__shfl_sync(0xffffffffu, w[0].x, from), __shfl_sync(0xffffffffu, w[0].y, from),
                                            __shfl_sync(0xffffffffu, w[0].z, from), __shfl_sync(0xffffffffu, w[0].w, from));
                const float wf[8] = {bf_lo(wn.x), bf_hi(wn.x), bf_lo(wn.y), bf_hi(wn.y), bf_lo(wn.z), bf_hi(wn.z), bf_lo(wn.w), bf_hi(wn.w)};
                mbar_wait_sleep(BAR(B_FULL + (s & 3)), s >> 2);
                const uint32_t xa = xa0 + (s & 3) * STAGE_BYTES;
                uint4 v[4];
#pragma unroll
                for (int r = 0; r < 4; r++) v[r] = lds128((xa ^ ((r & 1) << 6)) + r * 512);
                if (lane < (((s - sh) >> 1) == part ? 1 : 3)) mbar_arrive_after(BAR(B_HRD + s), v[0].x | v[1].x | v[2].x | v[3].x);
#pragma unroll
                for (int r = 0; r < 4; r++) {
                    const uint32_t xv[4] = {v[r].x, v[r].y, v[r].z, v[r].w};
#pragma unroll
                    for (int e = 0; e < 4; e++) {
                        const float a0 = bf_lo(xv[e]), a1 = bf_hi(xv[e]);
                        s1[r] += a0; s1[r] += a1;
                        s2[r] = fmaf(a1, a1, fmaf(a0, a0, s2[r]));
                        sx[r] = fmaf(a1, wf[2 * e + 1], fmaf(a0, wf[2 * e], sx[r]));
                    }
                    GAP("+f"(s1[r]), "+f"(s2[r]), "+f"(sx[r]));
                }
            }
            if (mt == 0) TRACE(211);
#pragma unroll
            for (int i = 1; i < 4; i++) w[i] = __ldg(reinterpret_cast<const uint4*>(P.wr + (eb ^ i) * 256 + lane * 8));
#define FOLD4(a, H, L) do { const bool uh = lane & (H), ul = lane & (L); \
                float p0 = (uh ? a[2] : a[0]) + __shfl_xor_sync(0xffffffffu, uh ? a[0] : a[2], H); \
                float p1 = (uh ? a[3] : a[1]) + __shfl_xor_sync(0xffffffffu, uh ? a[1] : a[3], H); \
                a[0] = (ul ? p1 : p0) + __shfl_xor_sync(0xffffffffu, ul ? p0 : p1, L); \
                _Pragma("unroll") for (int o = (L) >> 1; o; o >>= 1) a[0] += __shfl_xor_sync(0xffffffffu, a[0], o); } while (0)
            FOLD4(s1, 4, 2); FOLD4(s2, 4, 2); FOLD4(sx, 4, 2);
            if (!(lane & 1))
                st_relaxed128(&P.scr->xp[eb * S_ + j * 128 + xr0 + ((lane & 6) << 1)],
                              make_uint4(__float_as_uint(s1[0]), __float_as_uint(fmaf(s1[0] * (-1.0f / 256), s1[0], s2[0])), __float_as_uint(sx[0]), ep));
            wait_until(clk() + XPD);
            wait_until(t_in + XPT);
            {
                uint4 f[4];
                const uint4* xp = &P.scr->xp[j * 128 + mt];
                bool ok;
#pragma unroll
                for (int i = 0; i < 4; i++) f[i] = ld_relaxed128(xp + i * S_);
                float sw = sum8(w[0]) + sum8(w[1]), sw2;
                GAP("+f"(sw));
                sw2 = sum8(w[2]) + sum8(w[3]);
                GAP("+f"(sw2));
                sw = warp_sum(sw + sw2);
                do {
#pragma unroll
                    for (int i = 0; i < 4; i++) if (f[i].w != ep) f[i] = ld_relaxed128(xp + i * S_);
                    ok = f[0].w == ep && f[1].w == ep && f[2].w == ep && f[3].w == ep;
                } while (!__all_sync(0xffffffffu, ok) && IN_TIME());
                if (mt == 0) TRACE(224);
                const float mean = ((__uint_as_float(f[0].x) + __uint_as_float(f[1].x)) + (__uint_as_float(f[2].x) + __uint_as_float(f[3].x))) * (1.0f / D_);
                float m2 = 0.f, px = 0.f;
#pragma unroll
                for (int i = 0; i < 4; i++) {
                    const float d = fmaf(__uint_as_float(f[i].x), 1.0f / 256, -mean);
                    m2 += fmaf(d * 256.f, d, __uint_as_float(f[i].y));
                    px += __uint_as_float(f[i].z);
                }
                const float mb = rbf(mean);
                float sd, rinv;
                asm("sqrt.approx.ftz.f32 %0, %1;" : "=f"(sd) : "f"(rbf(rbf(fmaxf(m2 * (1.0f / D_), 0.f)) + 1e-5f)));
                asm("rcp.approx.ftz.f32 %0, %1;" : "=f"(rinv) : "f"(rbf(sd)));
                unsigned u = pack_bf(fmaf(-mb, sw, px) * rinv, 0.f);
                u = (u & 0x8000u) ? (~u & 0xffffu) : (u | 0x8000u);
                u = (u << 16) | (0xffffu - (unsigned)(j * 128 + mt));
                if (u == __reduce_max_sync(0xffffffffu, u))
                    *reinterpret_cast<uint4*>(smem + OFF_RED + aw * 16) = make_uint4(u, __float_as_uint(mb), __float_as_uint(rinv), 0);
                named_bar<4, 128>();
                if (aw == 0) {
                    const uint4 g = *reinterpret_cast<const uint4*>(smem + OFF_RED + (lane & 3) * 16);
                    if (g.x == __reduce_max_sync(0xffffffffu, g.x) && lane < 8) st_relaxed128(&P.scr->best[2 * b + (lane >> 2)], make_uint4(g.x, g.y, g.z, ep));
                }
                if (mt == 0) TRACE(212);
                *reinterpret_cast<float2*>(smem + OFF_MO + 4096 + mt * 8) = make_float2(mb, rinv);
                sts128(sb + OFF_MO + 5120 + mt * 16, pack_bf(-mb, -mb), pack_bf(-mb, 0.f), 0, 0);
                fence_async_smem();
                __syncwarp();
                if (lane == 0) mbar_arrive(BAR(B_STATS));
            }
            if (aw == 0) {
                uint4 f;
                wait_until(t_in + BPT);
                do { f = ld_relaxed128(&P.scr->best[2 * (grp * 16 + (lane & 15))]); } while (!__all_sync(0xffffffffu, f.w == ep) && IN_TIME());
                const unsigned key = __reduce_max_sync(0xffffffffu, f.x);
                if (lane < 16 && f.x == key) { *reinterpret_cast<uint4*>(smem + OFF_SEL) = f; mbar_arrive(BAR(B_SEL)); TRACE(200); }
                __syncwarp();
            }
        }
        if (moe) {
            const uint64_t pol = policy_evict_first();
            mbar_wait(BAR(B_SEL), 0);
            {
                const uint4 sl = lds128(sb + OFF_SEL);
                const float m = __uint_as_float(sl.y), ri = __uint_as_float(sl.z);
                const uint2 xv = __ldg(reinterpret_cast<const uint2*>(P.x + (size_t)(0xffff - (int)(sl.x & 0xffffu)) * D_ + c * (OWN / 2) + mt * 4));
                const char* w0 = WP0();
#pragma unroll
                for (int q = 0; q < NB; q++) buf[q] = ldg_stream(w0 + q * 8 * F_, pol);
                const uint32_t n0 = norm2(xv.x, m, ri), n1 = norm2(xv.y, m, ri);
                float* xn = reinterpret_cast<float*>(smem + OFF_XN) + mt;
                xn[0] = bf_lo(n0); xn[132] = bf_hi(n0); xn[264] = bf_lo(n1); xn[396] = bf_hi(n1);
            }
            named_bar<4, 128>();
            float ag[8];
#pragma unroll
            for (int i = 0; i < 8; i++) ag[i] = 0.f;
            uint32_t xq = sb + OFF_XN + (lane >> 3) * 528 + (aw >> 1) * (OWN / 4);
            uint32_t str = 8 * F_;
            const char* wp = WP0() + NB * 8 * F_;
            if (mt == 0) TRACE(213);
            mbar_wait_sleep(BAR(B_EPI + 3), 0);
            wait_until(clk() + GOD);
#pragma unroll 1
            for (int r = 0; r < GR + 4; r++, xq += 32) {
                if (r == GR - 1) { wp = reinterpret_cast<const char*>(P.wd + (size_t)(ci * 64 + c * 32) * D_ + (tid_now() - 256) * 8); str = 2 * D_; }
                if (r == GR + 3) str = 0;
#pragma unroll
                for (int h = 0; h < NB; h += 4) {
                    const uint4 m4 = lds128(xq + h * 4);
                    const uint32_t mv[4] = {m4.x, m4.y, m4.z, m4.w};
#pragma unroll
                    for (int q = 0; q < 4; q++) {
                        fma8(ag, buf[h + q], __uint_as_float(mv[q]));
                        GAP(R8(ag, 0));
                        ldg_stream_next(buf[h + q], wp, str, pol);
                    }
                }
                if (r != GR - 1) continue;
                const int lane = tid_now() & 31;
            {
                const bool uh = lane & 16, ul = lane & 8;
#pragma unroll
                for (int i = 0; i < 4; i++) ag[i] = (uh ? ag[i + 4] : ag[i]) + __shfl_xor_sync(0xffffffffu, uh ? ag[i] : ag[i + 4], 16);
#pragma unroll
                for (int i = 0; i < 2; i++) ag[i] = (ul ? ag[i + 2] : ag[i]) + __shfl_xor_sync(0xffffffffu, ul ? ag[i] : ag[i + 2], 8);
            }
            named_bar<4, 128>();
            float* ps = reinterpret_cast<float*>(smem + OFF_XN);
            *reinterpret_cast<float2*>(&ps[aw * 64 + (lane & 7) * 8 + (lane >> 3) * 2]) = make_float2(ag[0], ag[1]);
            named_bar<4, 128>();
            if (aw == 0) {
                const int o = (c ^ 1) * 32 + lane, m = c * 32 + lane;
                if (lane == 0) { mbar_expect_tx(BAR(B_PEER), 256); mbar_expect_tx(BAR(B_PR2), 2048); }
                const float go = ps[m] + ps[128 + m], uo = ps[64 + m] + ps[192 + m], gx = ps[o] + ps[128 + o], ux = ps[64 + o] + ps[192 + o];
                __syncwarp();
                st_async2(mapa(sb + OFF_RED + 256 + lane * 8, c ^ 1), gx, ux, mapa(BAR(B_PEER), c ^ 1));
                mbar_wait(BAR(B_GU), 0);
                mbar_wait_cluster(BAR(B_PEER), 0);
                const float2 pv = *reinterpret_cast<const float2*>(smem + OFF_RED + 256 + lane * 8);
                const float2 pq = *reinterpret_cast<const float2*>(smem + OFF_RED + lane * 8);
                hact[lane] = rbf(rbf(silu_f(rbf((go + pv.x) + pq.x))) * rbf((uo + pv.y) + pq.y));
                if (lane == 0) TRACE(214);
            }
            named_bar<4, 128>();
#pragma unroll
            for (int i = 0; i < 8; i++) ag[i] = 0.f;
            xq = sb + OFF_H - 32;
            }
            const int mt = tid_now() - 256;
            const unsigned ep = lds128(sb + OFF_SEL).w;
            if ((aw >> 1) != c) {
                const uint32_t rem = mapa(sb + OFF_XN + (mt & 63) * 16, c ^ 1);
                st_async4(rem, ag[0], ag[1], ag[2], ag[3], mapa(BAR(B_PR2), c ^ 1));
                st_async4(rem + 1024, ag[4], ag[5], ag[6], ag[7], mapa(BAR(B_PR2), c ^ 1));
                uint4* clr = &P.scr->part[(((ep + 1) & 1) * (NMOE / 2) + ci) * (D_ / 4) + mt];
                st_relaxed128(clr, make_uint4(0, 0, 0, 0));
                st_relaxed128(clr + 128, make_uint4(0, 0, 0, 0));
            } else {
                mbar_wait_cluster(BAR(B_PR2), 0);
                const float4 p0 = *reinterpret_cast<const float4*>(smem + OFF_XN + (mt & 63) * 16);
                const float4 p1 = *reinterpret_cast<const float4*>(smem + OFF_XN + 1024 + (mt & 63) * 16);
                uint4* dst = &P.scr->part[((ep & 1) * (NMOE / 2) + ci) * (D_ / 4) + mt];
                st_relaxed128(dst, make_uint4(~__float_as_uint(ag[0] + p0.x), __float_as_uint(ag[1] + p0.y), __float_as_uint(ag[2] + p0.z), __float_as_uint(ag[3] + p0.w)));
                st_relaxed128(dst + 128, make_uint4(~__float_as_uint(ag[4] + p1.x), __float_as_uint(ag[5] + p1.y), __float_as_uint(ag[6] + p1.z), __float_as_uint(ag[7] + p1.w)));
            }
            if (mt == 0) TRACE(215);
        }
        mbar_wait_sleep(BAR(B_SEL), 0);
        const uint4 sl = lds128(sb + OFF_SEL);
        const unsigned key = sl.x, ep = sl.w;
        const int sel = 0xffff - (int)(key & 0xffffu);
        const float2 st = make_float2(__uint_as_float(sl.y), __uint_as_float(sl.z));
        if ((sel >> 8) == (j >> 1)) {
            const int lane = tid_now() & 31;
            const uint4* src = &P.scr->part[((ep & 1) * (NMOE / 2) + (c * 4 + aw) * 7) * (D_ / 4) + (lane & 1) * 128 + eb * 32 + part * 16 + (lane >> 1)];
            float4* park = reinterpret_cast<float4*>(smem + OFF_PARK) + lane;
            const uint2 xv = __ldg(reinterpret_cast<const uint2*>(P.x + (size_t)sel * D_ + eb * 256 + part * 128 + lane * 4));
            AT_STEP(FRS);
            uint4 t[7];
#pragma unroll
            for (int u = 0; u < 7; u++) t[u].x = 0;
            bool ok;
            do {
#pragma unroll
                for (int u = 0; u < 7; u++) if (t[u].x == 0) t[u] = ld_relaxed128(src + u * (D_ / 4));
                ok = true;
#pragma unroll
                for (int u = 0; u < 7; u++) ok = ok && t[u].x != 0;
            } while (!__all_sync(0xffffffffu, ok) && IN_TIME());
            float4 a4 = make_float4(0.f, 0.f, 0.f, 0.f);
#pragma unroll
            for (int u = 0; u < 7; u++) {
                a4.x += __uint_as_float(~t[u].x); a4.y += __uint_as_float(t[u].y); a4.z += __uint_as_float(t[u].z); a4.w += __uint_as_float(t[u].w);
            }
            mbar_wait(BAR(he_bar(DEADH)), he_par(DEADH));
            park[aw * 32] = a4;
            named_bar<4, 128>();
            if (aw == 0) {
#pragma unroll
                for (int w = 1; w < 4; w++) { const float4 q = park[w * 32]; a4.x += q.x; a4.y += q.y; a4.z += q.z; a4.w += q.w; }
            }
            if (aw == 0 && (sel >> 7) != j) {
                st_async4(mapa(sb + OFF_RED + lane * 16, c ^ 1), a4.x, a4.y, a4.z, a4.w, mapa(BAR(B_FIN), c ^ 1));
            } else if (aw == 0) {
                if (lane == 0) mbar_expect_tx(BAR(B_FIN), 512);
                unsigned u = key >> 16;
                u = (u & 0x8000u) ? (u & 0x7fffu) : (~u & 0xffffu);
                const float sg = rbf(__fdividef(1.0f, 1.0f + __expf(-__uint_as_float(u << 16))));
                const uint32_t n0 = norm2(xv.x, st.x, st.y), n1 = norm2(xv.y, st.x, st.y);
                mbar_wait_cluster(BAR(B_FIN), 0);
                const float4 q = *reinterpret_cast<const float4*>(smem + OFF_RED + lane * 16);
                a4.x += q.x; a4.y += q.y; a4.z += q.z; a4.w += q.w;
                uint2 o;
                o.x = silu2(pack_bf(bf_lo(n0) + rbf(rbf(a4.x) * sg), bf_hi(n0) + rbf(rbf(a4.y) * sg)));
                o.y = silu2(pack_bf(bf_lo(n1) + rbf(rbf(a4.z) * sg), bf_hi(n1) + rbf(rbf(a4.w) * sg)));
                if (lane == 0) TRACE(216);
                mbar_wait(BAR(B_UPD), 0);
                const uint2 sr = *reinterpret_cast<const uint2*>(smem + OFF_SROW + lane * 8);
                *reinterpret_cast<uint2*>(P.out + (size_t)sel * D_ + eb * 256 + part * 128 + lane * 4) = make_uint2(bfma2(sr.x, o.x, xv.x), bfma2(sr.y, o.y, xv.y));
            }
        }
    } else {
        asm volatile("setmaxnreg.inc.sync.aligned.u32 %0;" ::"n"(CONS_REGS));
        const int wg = warp >> 2, wq = warp & 3;
        const int wt = tid & 127;
#define P4OK 0
        const int one = __shfl_sync(0xffffffffu, blockIdx.y + 1, 0);
        TRACE_C(50);
        float acc[128];
        const uint32_t rel_bar = mapa(BAR(B_EMPTY), (uint32_t)(wt >> 5) & 1);
        const bool rel_thr = (wt == 0) || (wt == 32);
#define RELEASE(s) do { if (rel_thr) mbar_arrive_cluster(rel_bar + 8u * (s)); } while (0)
        const uint32_t dA0 = desc_lo(SB0, 16) + wg * 512;
        constexpr uint32_t dBk0 = desc_lo(SB0 + A_BYTES, 16);
        constexpr uint32_t dBn0 = desc_lo(SB0, 4096);
        constexpr uint32_t ST = STAGE_BYTES >> 4;
        const int row_l = wg * 64 + wq * 16 + (lane >> 2);

        const uint32_t ioff = wq * 1024 + (lane >> 2) * 64 + (((lane & 3) ^ (lane >> 3)) << 4);
        uint32_t sdst = sb + (wg ? OFF_SP : OFF_X) + ioff;
        uint8_t* gdst = P.scr->ab + (size_t)(grp * 32 + 2 * j) * B_BYTES + ioff;
        asm volatile("" : "+l"(gdst), "+r"(sdst));

#define MMA1_H(O, s, first) do { _Pragma("unroll") for (int kk = 0; kk < 4; kk++) \
            wgmma128<O, 0>(acc, dA0 + (s) * ST + kk * 2, dBk0 + (s) * ST + kk * 2 + (O) * 16, !((first) && kk == 0)); } while (0)
#define WAIT_FULL(s, ph, it) do { mbar_wait(BAR(B_FULL + (s)), ph); TRACE_C(it); } while (0)
#define MMA1(s, first, rel) do { wg_fence(); MMA1_H(0, s, first); wg_commit(); wg_wait<1>(); rel; \
            wg_fence(); MMA1_H(64, s, first); wg_commit(); } while (0)
#define PROF5 0
#define WAIT_FULL_L(s, ph, it) WAIT_FULL(s, ph, it)
#define STEP1(s, ph, it, first, rel) do { WAIT_FULL_L(s, ph, it); MMA1(s, first, rel); } while (0)
        uint32_t xr[32];
        const uint32_t xad = sb + row_l * 128 + ((((lane & 4) + (lane & 3)) ^ (lane >> 2)) << 4);
#define XLOAD(s) do { if ((unsigned)(4 * o + (s) - sh - 2 * part) < 2u) { _Pragma("unroll") for (int h = 0; h < 4; h++) { \
            const uint4 u = lds128((xad ^ ((h >> 1) << 6)) + (s) * STAGE_BYTES + (h & 1) * 1024); \
            uint32_t* e = xr + 16 * ((s) & 1) + 4 * h; e[0] = u.x; e[1] = u.y; e[2] = u.z; e[3] = u.w; } \
            } } while (0)
#define XDONE(s) do { if ((unsigned)(4 * o + (s) - sh - 2 * part) < 2u && lane == 0) { const uint32_t* e = xr + 16 * ((s) & 1); \
            mbar_arrive_after(BAR(B_HRD + 4 * o + (s)), e[0] | e[4] | e[8] | e[12]); } } while (0)
#pragma unroll
        for (int i = 0; i < 32; i++) xr[i] = 0;
        TRACE_C(51);
#pragma unroll 1
        for (int o = 0; o < 3; o++) {
            STEP1(0, o & 1, 4 * o, o == 0, if (o) RELEASE(3); XDONE(-1)); XLOAD(0);
            STEP1(1, o & 1, 4 * o + 1, false, RELEASE(0); XDONE(0)); XLOAD(1);
            STEP1(2, o & 1, 4 * o + 2, false, RELEASE(1); XDONE(1)); XLOAD(2);
            STEP1(3, o & 1, 4 * o + 3, false, RELEASE(2); XDONE(2)); XLOAD(3);
        }
#define XSWAP() do { const bool odd = lane & 4; _Pragma("unroll") for (int i = 0; i < 24; i++) if (!(i & 8)) { \
            const uint32_t u0 = xr[i], u1 = xr[i + 8]; xr[i] = odd ? u1 : u0; xr[i + 8] = odd ? u0 : u1; } } while (0)
        XSWAP();
#define MEAN(O) wgmma128_k8<O>(acc, ((SB0 + OFF_MO + 5120) >> 4) + wg * 64, ((SB0 + OFF_MO) >> 4) + 2 * (O))
#define ROWSTAT() do { mbar_wait(BAR(B_STATS), 0); \
            st0 = *reinterpret_cast<const float2*>(smem + OFF_MO + 4096 + row_l * 8); \
            st1 = *reinterpret_cast<const float2*>(smem + OFF_MO + 4096 + row_l * 8 + 64); \
            rs0 = part ? -st0.y : st0.y; rs1 = part ? -st1.y : st1.y; } while (0)
#define PACK1(p, O, i) do { const float rs_ = ((i) & 1) ? rs1 : rs0; _Pragma("unroll") for (int e = 0; e < 4; e++) { \
                const int k = (O) + 16 * ((i) >> 1) + 4 * e + 2 * ((i) & 1); p[4 * (i) + e] = pack_bf(acc[k] * rs_, acc[k + 1] * rs_); } } while (0)
#define IOFF(O, i) ((O) * 256 + ((i) >> 1) * 4096 + ((i) & 1) * 512)
#define STS1(p, O, i) sts128(sdst + IOFF(O, i), p[4 * (i)], p[4 * (i) + 1], p[4 * (i) + 2], p[4 * (i) + 3])
#define STG1(p, O, i) stg128(gdst + IOFF(O, i), p[4 * (i)], p[4 * (i) + 1], p[4 * (i) + 2], p[4 * (i) + 3])
#define PIECES(p, O, G) PIECES_(p, O, G, 0, 8)
#define PIECES_(p, O, G, i0, i1) do { _Pragma("unroll") for (int i = (i0); i < (i1); i += 2) { PACK1(p, O, i); PACK1(p, O, i + 1); \
                ONCE(if (G) { STG1(p, O, i); STG1(p, O, i + 1); } else { STS1(p, O, i); STS1(p, O, i + 1); }); } } while (0)
#define BURST(ST, sp) do { unsigned tb = clk(); _Pragma("unroll") for (int i = 0; i < 16; i += 2) { \
                if (i < 8) { ST(pl, 0, i); ST(pl, 0, i + 1); } else { ST(pr, 64, i - 8); ST(pr, 64, i - 7); } \
                if (sp && i < 14) { tb += sp; while ((int)(clk() - tb) < 0) {} } } } while (0)
#define STAGED(i) do { fence_async_smem(); __syncwarp(); if (lane == 0) mbar_arrive(BAR(B_EPI + (i))); } while (0)
        float ac2[128];
#define MMA_F(O, aoff, boff, first) do { wg_fence(); _Pragma("unroll") for (int kk = 0; kk < 4; kk++) \
            wgmma128<O>(ac2, dA0 + ((aoff) >> 4) + kk * 2, dBn0 + ((boff) >> 4) + kk * 64, !((first) && kk == 0)); wg_commit(); } while (0)
#define LEFT16() do { mbar_wait(BAR(B_EPI + 1), 0); WAIT_FULL(0, 0, 16); MMA_F(0, 0, OFF_X, true); } while (0)
#define STAMP(k) do {} while (0)
        float2 st0, st1;
        float rs0, rs1;
        uint32_t pl[32], pr[32];
        if (wg == 0) {
            STEP1(0, 1, 12, false, RELEASE(3));
            STEP1(1, 1, 13, false, RELEASE(0));
            STEP1(2, 1, 14, false, RELEASE(1));
            STAMP(0);
            ROWSTAT();
            STAMP(1);
            wg_fence(); MEAN(64); MEAN(0);
            WAIT_FULL(3, 1, 15);
            STAMP(2);
            wg_fence(); MMA1_H(0, 3, false); wg_commit();
            MMA1_H(64, 3, false); wg_commit();
            named_arrive<5, 256>();
            const bool pub = c == 0;
            wg_wait<1>();
            fence_regs64<0>(acc);
            TRACE_C(52);
            STAMP(3);
            PIECES(pl, 0, pub);
            TRACE_C(53);
            STAMP(4);
            wg_wait<0>();
            fence_regs64<64>(acc);
            STAMP(5);
            RELEASE(2); RELEASE(3);
            if (tid == 0) mbar_arrive(BAR(B_W0D));
            mbar_wait(BAR(B_W1M), 0);
            TRACE_C(54);
            PIECES(pr, 64, pub);
            STAMP(6);
            if (pub) {
                __syncwarp();
                if (lane == 0) mbar_arrive(BAR(B_EPI + 0));
                mbar_wait(BAR(B_HS), 0);
                STAMP(7);
                BURST(STS1, BSP0);
            }
            STAGED(1);
            STAMP(8);
            if (!pub) {
                BURST(STG1, BSP1);
                __syncwarp();
                if (lane == 0) mbar_arrive(BAR(B_EPI + 0));
            }
            STAMP(9);
            LEFT16();
            STAMP(10);
        } else {
            wg_wait<0>(); RELEASE(3);
            ROWSTAT();
            wg_fence(); MEAN(64); MEAN(0); wg_commit();
            wg_wait<0>();
            if (lane == 0) mbar_arrive(BAR(B_W1M));
            named_bar<5, 256>();
            TRACE_C(12);
            STAMP(0);
            wg_fence(); MMA1_H(0, 0, false); MMA1_H(64, 0, false); wg_commit();
            MMA1(1, false, STAMP(1); RELEASE(0));
            wg_fence(); MMA1_H(0, 2, false); wg_commit();
            wg_wait<1>(); STAMP(2); RELEASE(1);
            mbar_wait(BAR(B_W0D), 0);
            wg_fence(); MMA1_H(0, 3, false); wg_commit();
            MMA1_H(64, 2, false); MMA1_H(64, 3, false); wg_commit();
            STAMP(3);
            wg_wait<1>();
            fence_regs64<0>(acc);
            TRACE_C(52);
            STAMP(4);
            PIECES_(pl, 0, false, 0, 4);
            STAMP(5);
            wg_wait<0>();
            fence_regs64<64>(acc);
            STAMP(6);
            RELEASE(2); RELEASE(3);
            PIECES_(pl, 0, false, 4, 8);
            TRACE_C(53);
            STAGED(2);
            STAMP(7);
            LEFT16();
            STAMP(8);
            TRACE_C(54);
            PIECES(pr, 64, false);
            STAGED(3);
            STAMP(9);
        }
        TRACE_C(55);

#define MMA2K(aoff, boff, k0) do { wg_fence(); _Pragma("unroll") \
        for (int kk = k0; kk < k0 + 2; kk++) { \
            wgmma128<0>(ac2, dA0 + ((aoff) >> 4) + kk * 2, dBn0 + ((boff) >> 4) + kk * 64, 1); \
            wgmma128<64>(ac2, dA0 + ((aoff) >> 4) + kk * 2, dBn0 + ((boff) >> 4) + kk * 64 + 1024, 1); } } while (0)
#define STEP2(s, ph, it) do { WAIT_FULL_L(s, ph, it); if (PROF5 && (it) < 34) STAMP(15 + (it) - 18); MMA2K((s) * STAGE_BYTES, b2_off(s), 0); \
            wg_commit(); wg_wait<1>(); RELEASE(((s) + 3) & 3); \
            MMA2K((s) * STAGE_BYTES, b2_off(s), 2); wg_commit(); } while (0)
#define MMA_H(O, aoff, boff) MMA_F(O, aoff, boff, false)
        MMA_F(64, 0, OFF_X + 16384, true);
        STAMP(11);
        mbar_wait(BAR(B_EPI + 2), 0); mbar_wait(BAR(B_FULL + 1), 0);
        STAMP(12);
        MMA_H(0, STAGE_BYTES, OFF_SP);
        wg_wait<1>(); STAMP(13); RELEASE(0);
        mbar_wait(BAR(B_EPI + 3), 0);
        STAMP(14);
        TRACE_C(17);
        MMA_H(64, STAGE_BYTES, OFF_SP + 16384);
        uint32_t g[32];
        const float mr0 = -st0.x * st0.y, mr1 = -st1.x * st1.y;
#define GATE(i) do { _Pragma("unroll") for (int e = (i); e < (i) + 4; e++) { \
                g[16 + e] = gate2(o == GATE_O ? xr[e] : xr[16 + e], ((i) & 4) ? st1.y : st0.y, ((i) & 4) ? mr1 : mr0); \
                g[e] = o == GATE_O ? g[16 + e] : g[e]; } } while (0)
#pragma unroll
        for (int i = 0; i < 32; i++) g[i] = 0;
#pragma unroll 1
        for (int o = 4;; o++) {
            const bool gt = (unsigned)(o - GATE_O) < 2u;
            STEP2(2, o & 1, 4 * o + 2);
            if (RS == 4 && o == 10) break;
            if (o == 4 && wt == 0) mbar_arrive(BAR(B_SPF));
            if (gt) GATE(0);
            STEP2(3, o & 1, 4 * o + 3);
            if (RS == 7 && o == 9) break;
            if (gt) GATE(4);
            STEP2(0, ~o & 1, 4 * o + 4);
            if (RS == 6 && o == 9) break;
            if (gt) GATE(8);
            STEP2(1, ~o & 1, 4 * o + 5);
            if (RS == 5 && o == 9) break;
            if (gt) GATE(12);
        }
#undef P4OK
#define P4OK 1
#define HSTEP(h) MMA_H(0, ha_off(h), hb_off(h))
        mbar_wait(BAR(B_SEL), 0);
        const uint32_t tag = __shfl_sync(0xffffffffu, *reinterpret_cast<volatile unsigned*>(smem + OFF_SEL + 12) & 1, 0);
        uint4* xdst = P.scr->xch + (size_t)(b ^ 16) * 2048 + tid_now();
        asm volatile("" : "+l"(xdst));
        __uint128_t sv[8];
#define SENT(tab, p) ((p) > 12 ? 8 : (int)((((unsigned long long)(tab) | 0x888888888888ull << (4 * SNDN)) << 4 >> (4 * (p))) & 15))
#define SEND(p) do { _Pragma("unroll") for (int v = 0; v < 8; v++) { \
            const bool s0 = v >= SENT(SND0, p) && v < SENT(SND0, (p) + 1), s1 = v >= SENT(SND1, p) && v < SENT(SND1, (p) + 1); \
            if (wg ? s1 : s0) st_relaxed128(xdst + v * 256, sv[v]); } } while (0)
        WAIT_FULL(hs(3), hp(3) ^ 1, 47 - RS);
        MMA_H(64, hs(3) * STAGE_BYTES, b2_off(hs(3)) + 16384);
        wg_wait<1>(); RELEASE(hs(2));
        MMA_H(0, hs(3) * STAGE_BYTES, b2_off(hs(3)));
        mbar_wait(BAR(hf_bar(0)), hf_par(0));
        HSTEP(0);
        wg_wait<2>();
        fence_regs64<64>(ac2);
        TRACE_C(56);
#pragma unroll
        for (int v = 0; v < 8; v++) {
            const int k = 64 + 16 * (v >> 1) + 2 * (v & 1);
            sv[v] = make128((pack_bf(ac2[k], ac2[k + 1]) & ~1u) | tag, pack_bf(ac2[k + 4], ac2[k + 5]), pack_bf(ac2[k + 8], ac2[k + 9]), pack_bf(ac2[k + 12], ac2[k + 13]));
        }
        SEND(0);
        wg_wait<1>(); RELEASE(hs(3));
        uint4 rv[8];
        const uint4* const xsrc = xdst + (part ? 16 * 2048 : -16 * 2048);
        unsigned probe = tag;
#define FETCH_RV() do { _Pragma("unroll") for (int v = 0; v < 8; v++) rv[v] = ld_relaxed128(xsrc + v * 256); } while (0)
#define PROBE() probe = ld_relaxed(&xsrc[7 * 256 + 31 - (tid_now() & 31)].x)
#define AFTER(h) do { \
            if (PRB == PRB1 ? NH - PRB == (h) : NH - PRB == (h) ? wg == 0 : NH - PRB1 == (h) && wg == 1) PROBE(); \
            if (RCV == RCV1 ? NH - RCV == (h) : NH - RCV == (h) ? wg == 0 : NH - RCV1 == (h) && wg == 1) ONCE(if (!((probe ^ tag) & 1)) FETCH_RV();); \
            if (STG && NH - 9 + STG == (h) && wg == 1) { \
                if (POLL1 && ((probe ^ tag) & 1)) {        \
                    _Pragma("unroll 1") for (int k = 0; k < POLL1; k++) { PROBE(); if (!((probe ^ tag) & 1)) { FETCH_RV(); break; } } } \
                named_bar<8, 256>(); } } while (0)
#define HALF(h) do { mbar_wait(BAR(hf_bar(h)), hf_par(h)); TRACE_C((h) + 7 >= NH ? 44 + 7 + (h) - NH : 63); HSTEP(h); SEND(h); \
            if ((h) + 6 < NH || (h) - 1 == DEADH) { wg_wait<1>(); RELEASE(he_bar((h) - 1) - B_EMPTY); } } while (0)
#define HALF_A(h) do { if ((h) < NH && (h) <= SNDN) HALF(h); } while (0)
#define HALF_B(h) do { if ((h) < NH && (h) > SNDN) { HALF(h); AFTER(h); } } while (0)
        HALF_A(1); HALF_A(2); HALF_A(3); HALF_A(4); HALF_A(5); HALF_A(6); HALF_A(7); HALF_A(8);
        TRACE_C(57);
#pragma unroll
        for (int v = 0; v < 8; v++) rv[v] = make_uint4(~tag, 0, 0, 0);
        AFTER(SNDN);
        HALF_B(1); HALF_B(2); HALF_B(3); HALF_B(4); HALF_B(5); HALF_B(6); HALF_B(7); HALF_B(8); HALF_B(9); HALF_B(10); HALF_B(11); HALF_B(12); HALF_B(13);
        if (STG && wg == 0) named_arrive<8, 256>();
        TRACE_C(58);
        const int t2 = tid_now();
        __nv_bfloat16* op = P.out + (size_t)(j * 128 + (t2 >> 5) * 16 + ((t2 >> 2) & 7)) * D_ + eb * 256 + part * 128 + (t2 & 3) * 8;
        asm volatile("" : "+l"(op));
        const int sl = 0xffff - (int)(*reinterpret_cast<volatile unsigned*>(smem + OFF_SEL) & 0xffffu) - j * 128 - (t2 >> 5) * 16;
        const bool lo = ((t2 >> 2) & 7) == sl, hi = ((t2 >> 2) & 7) + 8 == sl;
        if ((unsigned)sl < 16u) {
            mbar_wait(BAR(he_bar(DEADH)), he_par(DEADH));
#pragma unroll
            for (int i = 0; i < 32; i++) if ((i & 4) ? hi : lo) { g[i] = 0x3f803f80u; xr[i] = 0; }
        }
        while (true) {
            uint32_t bad = 0;
#pragma unroll
            for (int v = 0; v < 8; v++) bad |= rv[v].x ^ tag;
            if (__all_sync(0xffffffffu, !(bad & 1)) || !IN_TIME()) break;
            if ((t2 & 31) == 31) { while (((ld_relaxed(&xsrc[7 * 256].x) ^ tag) & 1) && IN_TIME()) {} }
            __syncwarp();
#pragma unroll
            for (int v = 0; v < 8; v++) rv[v] = ld_relaxed128(xsrc + v * 256);
        }
        TRACE_C(59);
        ONCE(_Pragma("unroll") for (int v = 0; v < 8; v++) {
            const int i = 4 * v;
            xr[i] = bfma2(rv[v].x & ~1u, g[i], xr[i]); xr[i + 1] = bfma2(rv[v].y, g[i + 1], xr[i + 1]);
            xr[i + 2] = bfma2(rv[v].z, g[i + 2], xr[i + 2]); xr[i + 3] = bfma2(rv[v].w, g[i + 3], xr[i + 3]);
        });
        wg_wait<0>();
        fence_regs64<0>(ac2);
        TRACE_C(60);
#pragma unroll
        for (int n = 0; n < 8; n += 2) {
            uint32_t o[8];
#pragma unroll
            for (int e = 0; e < 8; e++) {
                const int h = n >> 2, a = (n & 3) + (e >> 2), k = 16 * a + 2 * h + 4 * (e & 3), i = 8 * a + 4 * h + (e & 3);
                o[e] = bfma2(pack_bf(ac2[k], ac2[k + 1]), g[i], xr[i]);
            }
            ONCE(if ((n >> 2) ? hi : lo) {
                     sts128(sb + OFF_SROW + (n & 3) * 64 + (t2 & 3) * 16, o[0], o[1], o[2], o[3]);
                     sts128(sb + OFF_SROW + (n & 3) * 64 + 64 + (t2 & 3) * 16, o[4], o[5], o[6], o[7]);
                 } else {
                     stg128(op + (n >> 2) * 8 * D_ + (n & 3) * 32, o[0], o[1], o[2], o[3]);
                     stg128(op + (n >> 2) * 8 * D_ + (n & 3) * 32 + 32, o[4], o[5], o[6], o[7]);
                 });
        }
        if ((unsigned)sl < 16u) { __syncwarp(); if ((t2 & 31) == 0) mbar_arrive(BAR(B_UPD)); }
    }
}

typedef CUresult (*EncodeFn)(CUtensorMap*, CUtensorMapDataType, cuuint32_t, void*, const cuuint64_t*, const cuuint64_t*,
                             const cuuint32_t*, const cuuint32_t*, CUtensorMapInterleave, CUtensorMapSwizzle,
                             CUtensorMapL2promotion, CUtensorMapFloatOOBfill);

void make_map(EncodeFn fn, CUtensorMap* tm, const void* p, uint64_t rows, uint64_t cols) {
    cuuint64_t dims[2] = {cols, rows};
    cuuint64_t strides[1] = {cols * 2};
    cuuint32_t box[2] = {64, 128};
    cuuint32_t es[2] = {1, 1};
    fn(tm, CU_TENSOR_MAP_DATA_TYPE_BFLOAT16, 2, const_cast<void*>(p), dims, strides, box, es, CU_TENSOR_MAP_INTERLEAVE_NONE,
       CU_TENSOR_MAP_SWIZZLE_128B, CU_TENSOR_MAP_L2_PROMOTION_L2_128B, CU_TENSOR_MAP_FLOAT_OOB_FILL_NONE);
}

}

extern "C" void kernel_launch(void* const* d_in, const int* in_sizes, int n_in, void* d_out, int out_size) {
    (void)in_sizes; (void)n_in; (void)out_size;
    static EncodeFn fn = nullptr;
    static void* scr = nullptr;
    static bool by_sm = false;
    if (!fn) {
        void* p = nullptr;
        cudaDriverEntryPointQueryResult q;
        cudaGetDriverEntryPoint("cuTensorMapEncodeTiled", &p, cudaEnableDefault, &q);
        fn = (EncodeFn)p;
        cudaGetSymbolAddress(&scr, g_scr);
        int dev = 0, sms = 0;
        cudaGetDevice(&dev);
        cudaDeviceGetAttribute(&sms, cudaDevAttrMultiProcessorCount, dev);
        by_sm = sms == NCTA + 4;
        cudaFuncSetAttribute(by_sm ? fnet_fused_kernel<true> : fnet_fused_kernel<false>, cudaFuncAttributeMaxDynamicSharedMemorySize, SMEM_BYTES);
    }
    CUtensorMap tx, tdre, tdim, tcre, tcim;
    make_map(fn, &tx, d_in[0], S_, D_);
    make_map(fn, &tcre, d_in[1], S_, S_);
    make_map(fn, &tcim, d_in[2], S_, S_);
    make_map(fn, &tdre, d_in[3], D_, D_);
    make_map(fn, &tdim, d_in[4], D_, D_);
    Params P;
    P.x = (const __nv_bfloat16*)d_in[0];
    P.dre = (const __nv_bfloat16*)d_in[3];
    P.dim = (const __nv_bfloat16*)d_in[4];
    P.cre = (const __nv_bfloat16*)d_in[1];
    P.cim = (const __nv_bfloat16*)d_in[2];
    P.wr = (const __nv_bfloat16*)d_in[6];
    P.wg = (const __nv_bfloat16*)d_in[7];
    P.wu = (const __nv_bfloat16*)d_in[8];
    P.wd = (const __nv_bfloat16*)d_in[9];
    P.out = (__nv_bfloat16*)d_out;
    P.scr = (Scratch*)scr;
    if (by_sm) fnet_fused_kernel<true><<<NCTA + 4, NTHREADS, SMEM_BYTES, cudaStreamPerThread>>>(tx, tdre, tdim, tcre, tcim, P);
    else fnet_fused_kernel<false><<<NCTA + 4, NTHREADS, SMEM_BYTES, cudaStreamPerThread>>>(tx, tdre, tdim, tcre, tcim, P);
}
```

```cpp
#include <cuda_runtime.h>
#include <cuda_bf16.h>
#include <cuda.h>
#include <stdint.h>

#define PACE1 450
#define PACE2 1400
#define PACE3 2300
#define D0 4000
#define DGAP 800
#define DLAG 2
#define XPD 500
#define XPT 8400
#define BPT 12000
#define RSD 11000
#define GUS 29
#define CPN 4
#define GR 7
#define I0 0
#define SPW 5
#define SPG 700
#define DELAY0 2000
#define DELAY2 6000
#define SPACE0 1000
#define FRS 49
#define WS0 22
#define WS1 31
#define WS2 (42 - RS)
#define WS3 (45 - RS)
#define MSL 200
#define GATE_O 4
#define SNDN 7
#define SND0 0x8765432
#define SND1 0x7654321
#define STG 5
#define PRB 5
#define RCV 4
#define POLL1 2
#define PRB1 PRB
#define RCV1 RCV
#define FRSH 4
#define SLEEP_NS 80
#define GOD 100
#define WSL 40
#define BSP0 80
#define BSP1 110

#define RS 7
#define PROD_REGS 32
#define HELP_REGS 64
#define CONS_REGS 208
#define NB 8

namespace {

constexpr int S_ = 2048, D_ = 1024, F_ = 3584;
constexpr int NCTA = 128;
constexpr int OWN = GR * 128, SLR = (D_ - OWN) / 4;
constexpr int NMOE = 112;
constexpr uint32_t A_BYTES = 16384, B_BYTES = 32768, STAGE_BYTES = A_BYTES + B_BYTES;
constexpr uint32_t OFF_X = 4 * STAGE_BYTES;
constexpr uint32_t OFF_MO = OFF_X + 24576;
constexpr uint32_t OFF_SP = STAGE_BYTES + A_BYTES;
constexpr uint32_t OFF_BAR = OFF_X + 32768;
constexpr uint32_t OFF_XN = OFF_BAR + 304;
constexpr uint32_t OFF_RED = OFF_XN + 2112;
constexpr uint32_t OFF_H = OFF_RED + 512;
constexpr uint32_t OFF_SEL = OFF_H + 128;
constexpr uint32_t SMEM_BYTES = OFF_SEL + 16;
constexpr uint32_t SB0 = 1024;
constexpr int NTHREADS = 512;
static_assert(SMEM_BYTES <= 232448, "smem");
__host__ __device__ constexpr uint32_t b2_off(int s) { return s == 1 ? OFF_X : (s == 0 ? 3 : s == 2 ? 0 : 2) * STAGE_BYTES + A_BYTES; }
__host__ __device__ constexpr int hs(int i) { return (i + 4 - RS) & 3; }
__host__ __device__ constexpr int hp(int i) { return ((48 - RS + i) >> 2) & 1; }
constexpr int NH = 2 * RS;
constexpr int DEADH = NH - 7;
__host__ __device__ constexpr uint32_t ha_off(int h) {
    return h % 7 == 0 ? OFF_SP : h % 7 == 1 ? OFF_SP + 16384 : h % 7 == 6 ? b2_off(hs(3)) + 16384 : hs(h % 7 - 2) * STAGE_BYTES;
}
__host__ __device__ constexpr uint32_t hb_off(int h) { return b2_off(hs((h % 7) >> 1)) + (h % 7 & 1) * 16384; }

enum {
    B_FULL = 0, B_EMPTY = 4,
    B_EPI = 8,
    B_HRD = 12,
    B_DR = 17,
    B_RSD = 21,
    B_STATS,
    B_W1M, B_W0D,
    B_HS,
    B_SPF,
    B_HX,
    B_SEL = B_HX + 3, B_GU, B_PEER, B_PR2, B_FIN, B_UPD,
    B_COUNT
};
__host__ __device__ constexpr int hf_bar(int h) { return h % 7 == 1 ? B_HX : h % 7 == 3 ? B_HX + 1 : h % 7 == 6 ? B_HX + 2 : B_FULL + hs(h % 7 == 5 ? 3 : (h % 7) >> 1); }
__host__ __device__ constexpr int hf_par(int h) { return (h % 7 == 1 || h % 7 == 3 || h % 7 == 6 ? 0 : hp(h % 7 == 5 ? 3 : (h % 7) >> 1)) ^ (h / 7); }
__host__ __device__ constexpr int he_bar(int h) { return h < 2 ? B_EMPTY + hs(h) : h < 6 ? B_EPI + h - 2 : B_EMPTY + hs(h - 4); }
__host__ __device__ constexpr int he_par(int h) { return h < 2 ? hp(h) : h < 6 ? 1 : hp(h - 4); }
constexpr uint32_t OFF_PARK = ha_off(DEADH);
constexpr uint32_t OFF_GROW = OFF_PARK + 6144;
__host__ __device__ constexpr uint32_t bar_count(int i) {
    return i < B_EMPTY ? 1 : i < B_HRD || i == B_W1M ? 4 : i < B_DR ? 12 : i <= B_RSD || i == B_SPF ? 3 : i == B_STATS ? 5 : 1;
}
constexpr uint32_t OFF_MIR = OFF_BAR + 288;
static_assert(8 * B_COUNT <= 288 && OFF_MIR + 16 <= OFF_XN, "barriers");

struct Scratch {
    uint4 part[2 * (NMOE / 2) * (D_ / 4)];
    uint4 xp[4 * S_];
    uint2 rs[2 * D_];
    uint4 best[2 * NCTA];
    uint4 gu[4 * F_];
    unsigned long long abflag[8 * 16];
    unsigned epoch[NCTA];
    uint4 epoch2[4];
    alignas(1024) uint4 xch[NCTA * 2048];
    uint8_t ab[8u * 32u * 32768u];
};
__device__ __align__(1024) Scratch g_scr;
#define TRACE(i) do {} while (0)
#define TRACE_C(i) do {} while (0)
#define TRACE_G(i) do {} while (0)

__device__ __forceinline__ uint32_t smem_u32(const void* p) { return (uint32_t)__cvta_generic_to_shared(p); }
__device__ __forceinline__ void mbar_init(uint32_t bar, uint32_t cnt) {
    asm volatile("mbarrier.init.shared::cta.b64 [%0], %1;" ::"r"(bar), "r"(cnt) : "memory");
}
__device__ __forceinline__ unsigned clk_hi() { unsigned t; asm volatile("mov.u32 %0, %%clock_hi;" : "=r"(t)); return t; }
#define MBAR_WAIT_(name, sem, idle) \
__device__ __forceinline__ void name(uint32_t bar, uint32_t parity, unsigned dl) { \
    asm volatile("{\n.reg .pred p;\n.reg .b32 t;\nL:\nmbarrier.try_wait.parity" sem ".shared::cta.b64 p, [%0], %1;\n@p bra D;\n" idle \
                 "mov.u32 t, %%clock_hi;\nsetp.le.u32 p, t, %2;\n@p bra L;\nD:\n}" ::"r"(bar), "r"(parity), "r"(dl), "n"(SLEEP_NS) : "memory"); }
MBAR_WAIT_(mbar_wait_, "", "")
MBAR_WAIT_(mbar_wait_sleep_, "", "nanosleep.u32 %3;\n")
MBAR_WAIT_(mbar_wait_cluster_, ".acquire.cluster", "")
#define mbar_wait(bar, parity) mbar_wait_(bar, parity, dl)
#define mbar_wait_sleep(bar, parity) mbar_wait_sleep_(bar, parity, dl)
#define mbar_wait_cluster(bar, parity) mbar_wait_cluster_(bar, parity, dl)
#define IN_TIME() (clk_hi() <= dl)
__device__ __forceinline__ void st_async2(uint32_t dst, float a, float b, uint32_t bar) {
    asm volatile("st.async.weak.shared::cluster.mbarrier::complete_tx::bytes.v2.f32 [%0], {%1, %2}, [%3];" ::"r"(dst), "f"(a), "f"(b), "r"(bar) : "memory");
}
__device__ __forceinline__ void st_async4(uint32_t dst, float a, float b, float c, float d, uint32_t bar) {
    asm volatile("st.async.weak.shared::cluster.mbarrier::complete_tx::bytes.v4.f32 [%0], {%1, %2, %3, %4}, [%5];"
                 ::"r"(dst), "f"(a), "f"(b), "f"(c), "f"(d), "r"(bar) : "memory");
}
__device__ __forceinline__ void mbar_arrive(uint32_t bar) {
    asm volatile("mbarrier.arrive.shared::cta.b64 _, [%0];" ::"r"(bar) : "memory");
}
__device__ __forceinline__ void mbar_arrive_after(uint32_t bar, uint32_t data) { mbar_arrive(bar + (data & blockIdx.y)); }
__device__ __forceinline__ void mbar_arrive_cluster(uint32_t cluster_bar) {
    asm volatile("mbarrier.arrive.shared::cluster.b64 _, [%0];" ::"r"(cluster_bar) : "memory");
}
__device__ __forceinline__ void mbar_expect_tx(uint32_t bar, uint32_t bytes) {
    asm volatile("mbarrier.arrive.expect_tx.shared::cta.b64 _, [%0], %1;" ::"r"(bar), "r"(bytes) : "memory");
}
__device__ __forceinline__ bool elect_one() {
    uint32_t p;
    asm volatile("{\n.reg .pred p;\nelect.sync _|p, 0xffffffff;\nselp.u32 %0, 1, 0, p;\n}" : "=r"(p));
    return p;
}
__device__ __forceinline__ uint32_t mapa(uint32_t addr, uint32_t rank) {
    uint32_t r;
    asm("mapa.shared::cluster.u32 %0, %1, %2;" : "=r"(r) : "r"(addr), "r"(rank));
    return r;
}
__device__ __forceinline__ void tma_2d(uint32_t dst, const CUtensorMap* tm, int c0, int c1, uint32_t bar) {
    asm volatile("cp.async.bulk.tensor.2d.shared::cluster.global.mbarrier::complete_tx::bytes [%0], [%1, {%3, %4}], [%2];"
                 ::"r"(dst), "l"(tm), "r"(bar), "r"(c0), "r"(c1) : "memory");
}
__device__ __forceinline__ void tma_2d_mc(uint32_t dst, const CUtensorMap* tm, int c0, int c1, uint32_t bar) {
    asm volatile("cp.async.bulk.tensor.2d.shared::cluster.global.mbarrier::complete_tx::bytes.multicast::cluster [%0], [%1, {%3, %4}], [%2], %5;"
                 ::"r"(dst), "l"(tm), "r"(bar), "r"(c0), "r"(c1), "h"((uint16_t)3) : "memory");
}
__device__ __forceinline__ void bulk_g2s_mc(uint32_t dst, const void* src, uint32_t bytes, uint32_t bar) {
    asm volatile("cp.async.bulk.shared::cluster.global.mbarrier::complete_tx::bytes.multicast::cluster [%0], [%1], %2, [%3], %4;"
                 ::"r"(dst), "l"(src), "r"(bytes), "r"(bar), "h"((uint16_t)3) : "memory");
}
__device__ __forceinline__ void bulk_g2s(uint32_t dst, const void* src, uint32_t bytes, uint32_t bar) {
    asm volatile("cp.async.bulk.shared::cluster.global.mbarrier::complete_tx::bytes [%0], [%1], %2, [%3];"
                 ::"r"(dst), "l"(src), "r"(bytes), "r"(bar) : "memory");
}
__device__ __forceinline__ void fence_async_smem() { asm volatile("fence.proxy.async.shared::cta;" ::: "memory"); }
__device__ __forceinline__ void prefetch_tmap(const CUtensorMap* tm) {
    asm volatile("prefetch.tensormap [%0];" ::"l"(tm) : "memory");
}
__device__ __forceinline__ unsigned long long ld_relaxed64(const unsigned long long* p) {
    unsigned long long v; asm volatile("ld.relaxed.gpu.global.u64 %0, [%1];" : "=l"(v) : "l"(p) : "memory"); return v;
}
__device__ __forceinline__ unsigned ld_relaxed8(const uint8_t* p) {
    unsigned v; asm volatile("ld.relaxed.gpu.global.u8 %0, [%1];" : "=r"(v) : "l"(p) : "memory"); return v;
}
__device__ __forceinline__ unsigned load_epoch(const unsigned* p) {
    unsigned v; asm volatile("ld.global.u32 %0, [%1];" : "=r"(v) : "l"(p) : "memory"); return v + 1;
}
__device__ __forceinline__ unsigned ld_relaxed(const unsigned* p) {
    unsigned v; asm volatile("ld.relaxed.gpu.global.u32 %0, [%1];" : "=r"(v) : "l"(p) : "memory"); return v;
}
__device__ __forceinline__ uint4 ld_relaxed128(const uint4* p) {
    uint4 v;
    asm volatile("{\n.reg .b128 t;\n.reg .b64 lo, hi;\nld.relaxed.gpu.global.b128 t, [%4];\nmov.b128 {lo, hi}, t;\n"
                 "mov.b64 {%0, %1}, lo;\nmov.b64 {%2, %3}, hi;\n}"
                 : "=r"(v.x), "=r"(v.y), "=r"(v.z), "=r"(v.w) : "l"(p) : "memory");
    return v;
}
__device__ __forceinline__ void st_relaxed128(uint4* p, const uint4& v) {
    asm volatile("{\n.reg .b128 t;\n.reg .b64 lo, hi;\nmov.b64 lo, {%1, %2};\nmov.b64 hi, {%3, %4};\nmov.b128 t, {lo, hi};\n"
                 "st.relaxed.gpu.global.b128 [%0], t;\n}"
                 ::"l"(p), "r"(v.x), "r"(v.y), "r"(v.z), "r"(v.w) : "memory");
}
__device__ __forceinline__ __uint128_t make128(uint32_t a, uint32_t b, uint32_t c, uint32_t d) {
    __uint128_t v;
    asm volatile("{\n.reg .b64 lo, hi;\nmov.b64 lo, {%1, %2};\nmov.b64 hi, {%3, %4};\nmov.b128 %0, {lo, hi};\n}" : "=q"(v) : "r"(a), "r"(b), "r"(c), "r"(d));
    return v;
}
__device__ __forceinline__ void st_relaxed128(uint4* p, __uint128_t v) {
    asm volatile("st.relaxed.gpu.global.b128 [%0], %1;" ::"l"(p), "q"(v) : "memory");
}
__device__ __forceinline__ void st_relaxed64(uint2* p, uint32_t lo, uint32_t hi) {
    asm volatile("{\n.reg .b64 t;\nmov.b64 t, {%1, %2};\nst.relaxed.gpu.global.b64 [%0], t;\n}" ::"l"(p), "r"(lo), "r"(hi) : "memory");
}
__device__ __forceinline__ void stg128(void* p, uint32_t a, uint32_t b, uint32_t c, uint32_t d) {
    asm volatile("st.global.v4.u32 [%0], {%1,%2,%3,%4};" ::"l"(p), "r"(a), "r"(b), "r"(c), "r"(d) : "memory");
}
__device__ __forceinline__ void sts128(uint32_t p, uint32_t a, uint32_t b, uint32_t c, uint32_t d) {
    asm volatile("st.shared.v4.u32 [%0], {%1,%2,%3,%4};" ::"r"(p), "r"(a), "r"(b), "r"(c), "r"(d) : "memory");
}
__device__ __forceinline__ uint4 lds128(uint32_t p) {
    uint4 v;
    asm volatile("ld.shared.v4.u32 {%0,%1,%2,%3}, [%4];" : "=r"(v.x), "=r"(v.y), "=r"(v.z), "=r"(v.w) : "r"(p) : "memory");
    return v;
}
__device__ __forceinline__ void prefetch_l2(const void* p) { asm volatile("prefetch.global.L2 [%0];" ::"l"(p)); }
__device__ __forceinline__ void st_release8(void* p, unsigned v) {
    asm volatile("st.release.gpu.global.u8 [%0], %1;" ::"l"(p), "r"(v) : "memory");
}
__device__ __forceinline__ uint64_t policy_evict_first() {
    uint64_t pol;
    asm("createpolicy.fractional.L2::evict_first.b64 %0, 1.0;" : "=l"(pol));
    return pol;
}
__device__ __forceinline__ uint4 ldg_stream(const void* p, uint64_t pol) {
    uint4 v;
    asm volatile("ld.global.nc.L1::no_allocate.L2::cache_hint.v4.u32 {%0,%1,%2,%3}, [%4], %5;"
                 : "=r"(v.x), "=r"(v.y), "=r"(v.z), "=r"(v.w) : "l"(p), "l"(pol));
    return v;
}
__device__ __forceinline__ void ldg_stream_next(uint4& v, const char*& p, uint32_t stride, uint64_t pol) {
    asm volatile("{\n.reg .pred q;\nsetp.ne.u32 q, %5, 0;\n"
                 "@q ld.global.nc.L1::no_allocate.L2::cache_hint.v4.u32 {%0,%1,%2,%3}, [%4], %6;\nmad.wide.u32 %4, %5, 1, %4;\n}"
                 : "+r"(v.x), "+r"(v.y), "+r"(v.z), "+r"(v.w), "+l"(p) : "r"(stride), "l"(pol));
}
template <int ID, int N> __device__ __forceinline__ void named_arrive() { asm volatile("bar.arrive %0, %1;" ::"n"(ID), "n"(N) : "memory"); }
template <int ID, int N> __device__ __forceinline__ void named_bar() { asm volatile("bar.sync %0, %1;" ::"n"(ID), "n"(N) : "memory"); }

__device__ __forceinline__ float bf_lo(uint32_t u) { return __uint_as_float(u << 16); }
__device__ __forceinline__ float bf_hi(uint32_t u) { return __uint_as_float(u & 0xffff0000u); }
__device__ __forceinline__ uint32_t pack_bf(float lo, float hi) {
    uint32_t r; asm("cvt.rn.bf16x2.f32 %0, %1, %2;" : "=r"(r) : "f"(hi), "f"(lo)); return r;
}
__device__ __forceinline__ float rbf(float v) { return __uint_as_float(pack_bf(0.f, v)); }
__device__ __forceinline__ float silu_f(float z) { return __fdividef(z, 1.0f + __expf(-z)); }
__device__ __forceinline__ uint32_t bfma2(uint32_t a, uint32_t b, uint32_t c) {
    uint32_t r; asm("fma.rn.bf16x2 %0, %1, %2, %3;" : "=r"(r) : "r"(a), "r"(b), "r"(c)); return r;
}
__device__ __forceinline__ uint32_t norm2(uint32_t xv, float m, float rinv) {
    uint32_t t = pack_bf(bf_lo(xv) - m, bf_hi(xv) - m);
    return pack_bf(bf_lo(t) * rinv, bf_hi(t) * rinv);
}
__device__ __forceinline__ float gate1(float x, float rinv, float mr) {
    const float h = fmaf(x, 0.5f * rinv, 0.5f * mr);
    float t;
    asm("tanh.approx.f32 %0, %1;" : "=f"(t) : "f"(h));
    return fmaf(h, t, h);
}
__device__ __forceinline__ uint32_t gate2(uint32_t xv, float rinv, float mr) {
    return pack_bf(gate1(bf_lo(xv), rinv, mr), gate1(bf_hi(xv), rinv, mr));
}
__device__ __forceinline__ uint32_t silu2(uint32_t z) { return pack_bf(silu_f(bf_lo(z)), silu_f(bf_hi(z))); }

__device__ __forceinline__ void wg_fence() { asm volatile("wgmma.fence.sync.aligned;" ::: "memory"); }
__device__ __forceinline__ void wg_commit() { asm volatile("wgmma.commit_group.sync.aligned;" ::: "memory"); }
template <int N> __device__ __forceinline__ void wg_wait() { asm volatile("wgmma.wait_group.sync.aligned %0;" ::"n"(N) : "memory"); }

__host__ __device__ constexpr uint32_t desc_lo(uint32_t addr, uint32_t lbo) { return ((addr & 0x3FFFF) >> 4) | ((lbo >> 4) << 16); }

#define R8(a, o) "+f"(a[(o) + 0]), "+f"(a[(o) + 1]), "+f"(a[(o) + 2]), "+f"(a[(o) + 3]), \
                 "+f"(a[(o) + 4]), "+f"(a[(o) + 5]), "+f"(a[(o) + 6]), "+f"(a[(o) + 7])
#define R64(a, o) R8(a, (o) + 0), R8(a, (o) + 8), R8(a, (o) + 16), R8(a, (o) + 24), \
                  R8(a, (o) + 32), R8(a, (o) + 40), R8(a, (o) + 48), R8(a, (o) + 56)

template <int O, int TB = 1>
__device__ __forceinline__ void wgmma128(float (&a)[128], uint32_t da, uint32_t db, int scale_d) {
    asm volatile(
        "{\n.reg .pred p;\n.reg .b64 da, db;\nsetp.ne.b32 p, %66, 0;\n"
        "mov.b64 da, {%64, 0x40000040};\nmov.b64 db, {%65, %68};\n"
        "wgmma.mma_async.sync.aligned.m64n128k16.f32.bf16.bf16 "
        "{%0,%1,%2,%3,%4,%5,%6,%7,%8,%9,%10,%11,%12,%13,%14,%15,"
        "%16,%17,%18,%19,%20,%21,%22,%23,%24,%25,%26,%27,%28,%29,%30,%31,"
        "%32,%33,%34,%35,%36,%37,%38,%39,%40,%41,%42,%43,%44,%45,%46,%47,"
        "%48,%49,%50,%51,%52,%53,%54,%55,%56,%57,%58,%59,%60,%61,%62,%63},"
        "da, db, p, 1, 1, 0, %67;\n}"
        : R64(a, O)
        : "r"(da), "r"(db), "r"(scale_d), "n"(TB), "n"(TB ? 0x80000020 : 0x40000040));
}
template <int O>
__device__ __forceinline__ void wgmma128_k8(float (&a)[128], uint32_t da, uint32_t db) {
    asm volatile(
        "{\n.reg .b64 da, db;\nmov.b64 da, {%64, 8};\nmov.b64 db, {%65, 8};\n"
        "wgmma.mma_async.sync.aligned.m64n128k16.f32.bf16.bf16 "
        "{%0,%1,%2,%3,%4,%5,%6,%7,%8,%9,%10,%11,%12,%13,%14,%15,"
        "%16,%17,%18,%19,%20,%21,%22,%23,%24,%25,%26,%27,%28,%29,%30,%31,"
        "%32,%33,%34,%35,%36,%37,%38,%39,%40,%41,%42,%43,%44,%45,%46,%47,"
        "%48,%49,%50,%51,%52,%53,%54,%55,%56,%57,%58,%59,%60,%61,%62,%63},"
        "da, db, 1, 1, 1, 0, 0;\n}"
        : R64(a, O)
        : "r"(da), "r"(db));
}
template <int O>
__device__ __forceinline__ void fence_regs64(float (&a)[128]) {
    asm volatile("" : R64(a, O)::"memory");
}

struct Params {
    const __nv_bfloat16* x;
    const __nv_bfloat16* dre;
    const __nv_bfloat16* dim;
    const __nv_bfloat16* cre;
    const __nv_bfloat16* cim;
    const __nv_bfloat16* wr;
    const __nv_bfloat16* wg;
    const __nv_bfloat16* wu;
    const __nv_bfloat16* wd;
    __nv_bfloat16* out;
    Scratch* scr;
};

__device__ __forceinline__ float warp_sum(float v) {
#pragma unroll
    for (int o = 16; o; o >>= 1) v += __shfl_xor_sync(0xffffffffu, v, o);
    return v;
}
__device__ __forceinline__ float sum8(const uint4& v) {
    return ((bf_lo(v.x) + bf_hi(v.x)) + (bf_lo(v.y) + bf_hi(v.y))) + ((bf_lo(v.z) + bf_hi(v.z)) + (bf_lo(v.w) + bf_hi(v.w)));
}
__device__ __forceinline__ void fma8(float* acc, const uint4& w, float s) {
    acc[0] = fmaf(s, bf_lo(w.x), acc[0]); acc[1] = fmaf(s, bf_hi(w.x), acc[1]); acc[2] = fmaf(s, bf_lo(w.y), acc[2]); acc[3] = fmaf(s, bf_hi(w.y), acc[3]);
    acc[4] = fmaf(s, bf_lo(w.z), acc[4]); acc[5] = fmaf(s, bf_hi(w.z), acc[5]); acc[6] = fmaf(s, bf_lo(w.w), acc[6]); acc[7] = fmaf(s, bf_hi(w.w), acc[7]);
}
__device__ __forceinline__ int tid_now() { int t; asm volatile("mov.u32 %0, %%tid.x;" : "=r"(t)); return t; }

#define GAP(...) do { asm volatile("" : __VA_ARGS__); \
    asm volatile("{\n.reg .pred p;\n.reg .b32 t;\nL: mov.u32 t, %clock_hi;\nsetp.eq.u32 p, t, 0xffffffff;\n@p bra L;\n}"); } while (0)
#define ONCE(...) do { int z_ = one; _Pragma("unroll 1") do { __VA_ARGS__ } while (--z_); } while (0)
__device__ __forceinline__ unsigned clk() { unsigned t; asm volatile("mov.u32 %0, %%clock;" : "=r"(t)); return t; }
__device__ __forceinline__ unsigned keep(unsigned t) { return __shfl_sync(0xffffffffu, t + (threadIdx.x & 31), 0); }
__device__ __forceinline__ void wait_until(unsigned t) { while ((int)(clk() - t) < 0) { if (WSL) __nanosleep(WSL); } }

__device__ __forceinline__ void spare_cta(const Params& P, uint8_t* smem, uint32_t sb, int tid, int warp, int b) {
    const unsigned dl = keep(clk_hi() + 1);
    const unsigned t_in = keep(clk());
    unsigned t0 = t_in + I0;
    const int lane = tid & 31, e = b - NCTA;
    const unsigned ep = load_epoch(&P.scr->epoch2[e].x);
    const char* dsrc = reinterpret_cast<const char*>(((e >> 1) ? P.dim : P.dre) + (size_t)((e & 1) * 512 + (warp & 1) * 32 + 12) * D_);
    const char* wsrc = reinterpret_cast<const char*>(((warp & 1) ? P.wu : P.wg) + (size_t)(OWN + e * SLR) * F_);
    const uint64_t pol = policy_evict_first();
    const uint32_t bar = sb + 15872;
    constexpr int last = 8 + SLR / 2;
    float* xn = reinterpret_cast<float*>(smem);
    float* rsum = reinterpret_cast<float*>(smem + 15360);
    if (tid == 0) { for (int i = 0; i < SPW; i++) mbar_init(bar + 8 * i, 1); fence_async_smem(); }
    float ag[16];
#pragma unroll
    for (int i = 0; i < 16; i++) ag[i] = 0.f;
    int slot = 0, ph = 1;
#pragma unroll 1
    for (int n = -SPW; n < last; n++) {
        const uint32_t st = sb + 16384 + slot * 32768;
        if (n == 8) {
            if (warp == 15) {
                uint4 f;
                wait_until(t_in + BPT + 800);
                while (true) {
                    f = ld_relaxed128(&P.scr->best[2 * (e * 32 + (lane & 15))]);
                    if (__all_sync(0xffffffffu, f.w == ep) || !IN_TIME()) break;
                    __nanosleep(100);
                }
                const unsigned key = __reduce_max_sync(0xffffffffu, f.x);
                const int from = __ffs(__ballot_sync(0xffffffffu, f.x == key)) - 1;
                const float m = __uint_as_float(__shfl_sync(0xffffffffu, f.y, from)), ri = __uint_as_float(__shfl_sync(0xffffffffu, f.z, from));
                const uint32_t n0 = norm2(__ldg(reinterpret_cast<const uint32_t*>(P.x + (size_t)(0xffff - (int)(key & 0xffffu)) * D_ + OWN + e * SLR) + (lane & (SLR / 2 - 1))), m, ri);
                *reinterpret_cast<float2*>(xn + lane * 2) = make_float2(bf_lo(n0), bf_hi(n0));
            }
            __syncthreads();
            t0 = clk();
        }
        if (n >= 0) {
            mbar_wait(bar + 8 * slot, ph);
            if (n < 8) {
                float a0 = 0.f;
#pragma unroll 1
                for (int i = 0; i < 4; i++) a0 += sum8(lds128(st + warp * 2048 + i * 512 + lane * 16));
                a0 = warp_sum(a0);
                if (lane == 0) rsum[n * 16 + warp] = a0;
            } else if (warp < 14) {
                const float2 x2 = *reinterpret_cast<const float2*>(xn + (n - 8) * 2);
#pragma unroll
                for (int i = 0; i < 4; i++) fma8(ag + 8 * (i >> 1), lds128(st + i * 7168 + tid * 16), (i & 1) ? x2.y : x2.x);
            }
        }
        __syncthreads();
        if ((unsigned)n < 8 && tid < 16)
            st_relaxed64(&P.scr->rs[(e >> 1) * D_ + (e & 1) * 512 + (n * 4 + (tid >> 2)) * 16 + 12 + (tid & 3)], __float_as_uint(rsum[n * 16 + tid]), ep);
        const int m = n + SPW;
        if (m < last && warp >= 14) {
            while ((int)(clk() - t0) < 0) {}
            t0 += SPG;
            if (elect_one()) {
                if (warp == 14) mbar_expect_tx(bar + 8 * slot, m < 8 ? 32768 : 28672);
                if (m < 8) {
                    bulk_g2s(st + (warp & 1) * 16384, dsrc + (size_t)m * 64 * 2 * D_, 8192, bar + 8 * slot);
                    bulk_g2s(st + (warp & 1) * 16384 + 8192, dsrc + (size_t)(m * 64 + 16) * 2 * D_, 8192, bar + 8 * slot);
                } else {
                    asm volatile("cp.async.bulk.shared::cluster.global.mbarrier::complete_tx::bytes.L2::cache_hint [%0], [%1], %2, [%3], %4;"
                                 ::"r"(st + (warp & 1) * 14336), "l"(wsrc + (size_t)(m - 8) * 4 * F_), "r"(14336), "r"(bar + 8 * slot), "l"(pol) : "memory");
                }
            }
            __syncwarp();
        }
        if (++slot == SPW) { slot = 0; ph ^= 1; }
    }
    if (warp < 14) {
        float4* ps = reinterpret_cast<float4*>(smem + 16384) + tid * 2;
#pragma unroll
        for (int i = 0; i < 4; i++) ps[(i >> 1) * (F_ / 4) + (i & 1)] = make_float4(ag[4 * i], ag[4 * i + 1], ag[4 * i + 2], ag[4 * i + 3]);
    }
    __syncthreads();
    const uint32_t* ps = reinterpret_cast<const uint32_t*>(smem + 16384);
#pragma unroll 1
    for (int f = tid; f < F_; f += NTHREADS) st_relaxed128(&P.scr->gu[e * F_ + f], make_uint4(ps[f], ps[F_ + f], ep, 0));
    if (tid == 0) P.scr->epoch2[e].x = ep;
}

template <bool BY_SM>
__global__ void __cluster_dims__(2, 1, 1) __launch_bounds__(NTHREADS, 1)
fnet_fused_kernel(const __grid_constant__ CUtensorMap tm_x, const __grid_constant__ CUtensorMap tm_dre,
                  const __grid_constant__ CUtensorMap tm_dim, const __grid_constant__ CUtensorMap tm_cre,
                  const __grid_constant__ CUtensorMap tm_cim, const Params P) {
    extern __shared__ __align__(1024) uint8_t smem_[];
    const int tid = threadIdx.x, lane = tid & 31;
    const int c = blockIdx.x & 1;
    int b = blockIdx.x;
    if (BY_SM) {
        unsigned sm; asm volatile("mov.u32 %0, %%smid;" : "=r"(sm));
        const int t = sm >> 1;
        const int u = t - 32;
        const int pr = u < 0 ? t : u < 28 ? t + 1 + ((u * 37) >> 8) : u < 30 ? t + 4 : (t - 58) * 8;
        b = pr * 2 + c;
    }
    const uint32_t sb = SB0 | (c << 24);
    uint8_t* const smem = reinterpret_cast<uint8_t*>(__cvta_shared_to_generic(sb));
    const int grp = b >> 4;
    const int part = grp & 1;
    const int eb = grp >> 1;
    const int j = b & 15;
    const int sh = eb != 0;
    const int ci = b >> 1;
    const bool moe = b < NMOE;
#define KBLK(it) ((it) <= 4 ? (4 * eb - sh + (it)) ^ sh : 4 * eb - sh + (it) - (4 * eb - sh + (it) > 15 ? 15 : 0))
    const uint32_t bar0 = sb + OFF_BAR;
#define BAR(i) (bar0 + 8u * (i))
#define CLUSTER_ARRIVE() asm volatile("barrier.cluster.arrive.relaxed.aligned;" ::: "memory")
#define CLUSTER_WAIT() asm volatile("barrier.cluster.wait.aligned;" ::: "memory")
#define FENCE_INIT() asm volatile("fence.mbarrier_init.release.cluster;" ::: "memory")
#define TE(i)
    const int warp = __shfl_sync(0xffffffffu, tid >> 5, 0);
    TE(0);
    if (warp == 0 && elect_one()) {
#pragma unroll
        for (int s = 0; s < 4; s++) mbar_init(BAR(B_FULL + s), 1);
        FENCE_INIT();
    }
    __syncwarp();
    CLUSTER_ARRIVE();
    TE(1);
    if (warp == 1 && elect_one()) prefetch_tmap(part ? &tm_dim : &tm_dre);
    const bool first = warp == 0 && b < NCTA;
    if (first && elect_one()) {
        mbar_expect_tx(BAR(B_FULL + 0), STAGE_BYTES);
        tma_2d(sb, &tm_x, 0, j * 128, BAR(B_FULL + 0));
    }
    __syncwarp();
    TE(2);
    CLUSTER_WAIT();
    TE(3);
    if (first && elect_one()) tma_2d_mc(sb + A_BYTES + c * 16384, part ? &tm_dim : &tm_dre, 0, eb * 256 + 128 * (c ^ part), BAR(B_FULL + 0));
    __syncwarp();
    const unsigned t_first = keep(clk());
    if ((warp == 3 || warp == 12) && elect_one()) {
        if (warp != 3) {
#pragma unroll
            for (int s = B_EMPTY; s < 20; s++) mbar_init(BAR(s), bar_count(s));
        } else {
#pragma unroll
            for (int s = 20; s < B_COUNT; s++) mbar_init(BAR(s), bar_count(s));
            *reinterpret_cast<uint4*>(smem + OFF_MIR) = make_uint4(0, 0, 0, 0);
        }
        FENCE_INIT();
    }
    __syncwarp();
    if (warp == 12 && b < NCTA) {
        named_arrive<0, NTHREADS>();
        if (elect_one()) {
            mbar_expect_tx(BAR(B_FULL + 1), STAGE_BYTES);
            while ((int)(clk() - t_first) < PACE1) {}
            tma_2d(sb + STAGE_BYTES, &tm_x, KBLK(1) * 64, j * 128, BAR(B_FULL + 1));
            tma_2d_mc(sb + STAGE_BYTES + A_BYTES + c * 16384, part ? &tm_dim : &tm_dre, KBLK(1) * 64, eb * 256 + 128 * (c ^ part), BAR(B_FULL + 1));
        }
        __syncwarp();
    } else {
        named_bar<0, NTHREADS>();
    }
    if (__popc(smem_u32(smem_) ^ sb) > blockIdx.y) return;
    if (__builtin_expect(b >= NCTA, 0)) { spare_cta(P, smem, sb, tid, warp, b); return; }

    const unsigned dl = keep(clk_hi() + 1);
    if (warp >= 12) {
        asm volatile("setmaxnreg.dec.sync.aligned.u32 %0;" ::"n"(PROD_REGS));
        if (warp == 12) {
            const CUtensorMap* tmD = part ? &tm_dim : &tm_dre;
            const CUtensorMap* tmC = part ? &tm_cim : &tm_cre;
            const int row0 = j * 128, drow = eb * 256 + 128 * (c ^ part), q0 = j >> 1;
            if (elect_one()) {
                const unsigned t0 = t_first;
#pragma unroll 1
                for (int it = 2; it < 16; it++) {
                    const int s = it & 3;
                    const uint32_t st = sb + s * STAGE_BYTES, fb = BAR(B_FULL + s);
                    if (it < 4) {
                        wait_until(t0 + (it == 2 ? PACE2 : PACE3));
                    } else {
                        mbar_wait(BAR(B_EMPTY + s), ((it >> 2) & 1) ^ 1);
                        if (it < 8 + sh) mbar_wait(BAR(B_HRD + it - 4), 0);
                    }
                    mbar_expect_tx(fb, STAGE_BYTES);
                    const int kc = KBLK(it) * 64;
                    tma_2d(st, &tm_x, kc, row0, fb);
                    tma_2d_mc(st + A_BYTES + c * 16384, tmD, kc, drow, fb);
                    TRACE(128 + it);
                    if (it == 4) { prefetch_tmap(&tm_cre); prefetch_tmap(&tm_cim); }
                }
                const unsigned ep = load_epoch(&P.scr->epoch[b]);
#pragma unroll 1
                for (int i = 0; i < 2; i++) {
                    mbar_wait(BAR(B_EMPTY + i), 1);
                    mbar_expect_tx(BAR(B_FULL + i), A_BYTES);
                    tma_2d(sb + i * STAGE_BYTES, tmC, (2 * j + i) * 64, row0, BAR(B_FULL + i));
                    TRACE(128 + 16 + i);
                }
                const uint8_t* abg = P.scr->ab + (size_t)grp * 32 * B_BYTES;
                int it = 18;
                unsigned have = 0;
                auto seen = [&](int word, unsigned want) {
                    if ((have & want) == want) return;
                    do {
                        asm volatile("ld.acquire.cta.shared::cta.u32 %0, [%1];" : "=r"(have) : "r"(sb + OFF_MIR + 4 * word) : "memory");
                    } while ((have & want) != want && IN_TIME());
                    asm volatile("fence.proxy.async.global;" ::: "memory");
                };
                unsigned long long rdy = (unsigned long long)(~ep & 0xffu) * 0x0101010101010101ull;
#pragma unroll 1
                for (int cl = 0; cl < 4; cl++) {
                    const int ko = ((cl & 1) << 1) + (cl >> 1);
#pragma unroll 1
                    for (int n = cl < 2; n < (cl < 3 ? 8 : 8 - RS); n++, it++) {
                        const int q = (q0 + n) & 7, kb = n ? 4 * q + ko : 2 * (j ^ 1) + cl - 2;
                        const int s = it & 3;
                        const uint32_t fb = BAR(B_FULL + s), bs = sb + b2_off(s);
                        if (it != 19) {
                            mbar_wait(BAR(B_EMPTY + s), ((it >> 2) & 1) ^ 1); mbar_expect_tx(fb, STAGE_BYTES);
                            tma_2d(sb + s * STAGE_BYTES, tmC, kb * 64, row0, fb);
                        }
                        if (it == 18) {
                            mbar_wait(BAR(B_EMPTY + 3), 1); mbar_expect_tx(BAR(B_FULL + 3), STAGE_BYTES);
                            tma_2d(sb + 3 * STAGE_BYTES, tmC, ((q + 1) & 7) * 256, row0, BAR(B_FULL + 3));
                        }
                        if (cl == 0) {
                            if (((unsigned)(rdy >> (8 * q)) & 0xffu) != (ep & 0xffu)) {
                                do { rdy = ld_relaxed64(&P.scr->abflag[grp * 16]); } while (((unsigned)(rdy >> (8 * q)) & 0xffu) != (ep & 0xffu) && IN_TIME());
                                asm volatile("fence.acquire.gpu;\nfence.proxy.async.global;" ::: "memory");
                            }
                        } else {
                            seen(0, 1u << (8 * (n ? cl : 2 * cl - 3 - c) + q));
                        }
                        if (it == 18) TRACE(199);
                        if (n) bulk_g2s_mc(bs + c * 16384, abg + (size_t)kb * B_BYTES + c * 16384, 16384, fb);
                        else bulk_g2s(bs, abg + (size_t)kb * B_BYTES, B_BYTES, fb);
                        *reinterpret_cast<volatile int*>(smem + OFF_MIR + 8) = it;
                        TRACE(128 + it);
                    }
                }
                have = 0;
                seen(1, 0xff000000u);
                const uint8_t* abf = P.scr->ab + (size_t)(grp ^ 1) * 32 * B_BYTES + 16384;
                const uint8_t* const ab0 = part ? abf : abg;
                const uint8_t* const ab1 = part ? abg : abf;
                mbar_wait(BAR(B_SPF), 0);
#pragma unroll
                for (int h = 0; h < NH; h++) {
                    const int kb = 4 * ((q0 + 8 - RS + (h >> 1)) & 7) + 3;
                    const uint32_t fb = BAR(hf_bar(h));
                    if (h >= 7) mbar_wait(BAR(he_bar(h - 7)), he_par(h - 7));
                    else if (h != 1 && h != 3 && h != 6) { const int i = h == 5 ? 3 : h >> 1; mbar_wait(BAR(B_EMPTY + hs(i)), hp(i) ^ 1); }
                    mbar_expect_tx(fb, 32768);
                    tma_2d(sb + ha_off(h), (h & 1) ? &tm_cim : &tm_cre, kb * 64, row0, fb);
                    bulk_g2s_mc(sb + hb_off(h) + c * 8192, ((h & 1) ? ab1 : ab0) + (size_t)kb * B_BYTES + c * 8192, 8192, fb);
                    if (h == NH - FRSH) *reinterpret_cast<volatile int*>(smem + OFF_MIR + 8) = FRS;
                    TRACE(128 + 48 - RS + h);
                }
                P.scr->epoch[b] = ep;
            }
        } else {
          const unsigned t_in = t_first;
          const unsigned ep = load_epoch(&P.scr->epoch[b]);
          {
            if (lane == 0) TRACE(227);
#pragma unroll 1
            for (int k = -DLAG; k < 4; k++) {
                const int r = 4 * (warp - 13) + k;
                if (k + DLAG < 4) {
                    wait_until(t_in + D0 + (k + DLAG) * DGAP);
                    if (elect_one()) {
                        mbar_expect_tx(BAR(B_DR + k + DLAG), 2048);
                        bulk_g2s(sb + OFF_X + (r + DLAG) * 2048, (part ? P.dim : P.dre) + (size_t)(eb * 256 + j * 16 + r + DLAG) * D_, 2048, BAR(B_DR + k + DLAG));
                    }
                    __syncwarp();
                }
                if (k < 0) continue;
                mbar_wait_sleep(BAR(B_DR + k), 0);
                if (tid == 13 * 32) TRACE(228 + k);
                uint4 v[4];
#pragma unroll
                for (int i = 0; i < 4; i++) v[i] = lds128(sb + OFF_X + r * 2048 + i * 512 + lane * 16);
                float a0 = 0.f;
#pragma unroll
                for (int i = 0; i < 4; i++) { a0 += sum8(v[i]); if (i & 1) GAP("+f"(a0)); }
                a0 = warp_sum(a0);
                if (lane == 0) reinterpret_cast<float*>(smem + OFF_H)[r] = a0;
            }
#pragma unroll 1
            for (int i = warp - 13; i < CPN; i += 3)
                prefetch_l2((part ? P.cim : P.cre) + (size_t)(j * 128 + eb * 32 + lane) * S_ + (i < 2 ? 2 * j + i : 4 * (((j >> 1) + i - 1) & 7)) * 64);
            if (lane == 0) TRACE(217 + warp - 13);
          }
          if (lane == 0) mbar_arrive(BAR(B_RSD));
          if (warp == 14) {
#define AT_STEP(n) do { while (*reinterpret_cast<volatile int*>(smem + OFF_MIR + 8) < (n) && IN_TIME()) __nanosleep(MSL); } while (0)
#define WATCH(g, word, want) do { const uint8_t* fp = reinterpret_cast<const uint8_t*>(&P.scr->abflag[(g) * 16]) + lane; \
                unsigned known = 0; \
                while (true) { \
                    const unsigned m = __ballot_sync(0xffffffffu, ld_relaxed8(fp) == (ep & 0xffu)); \
                    if (m != known) { \
                        known = m; \
                        asm volatile("fence.acquire.gpu;" ::: "memory"); \
                        __syncwarp(); \
                        if (lane == 0) asm volatile("st.release.cta.shared::cta.u32 [%0], %1;" ::"r"(sb + OFF_MIR + 4 * (word)), "r"(m) : "memory"); \
                    } \
                    if ((m & (want)) == (want) || !IN_TIME()) break; \
                    __nanosleep(MSL); \
                } } while (0)
            AT_STEP(WS0);
            WATCH(grp, 0, 0xffffu);
            if (moe) {
                uint4 g[4];
                const uint4* gp = &P.scr->gu[ci * 64 + c * 32 + lane];
                AT_STEP(GUS);
                while (true) {
                    bool ok = true;
#pragma unroll
                    for (int i = 0; i < 4; i++) { g[i] = ld_relaxed128(gp + i * F_); ok = ok && g[i].z == ep; }
                    if (__all_sync(0xffffffffu, ok) || !IN_TIME()) break;
                    __nanosleep(MSL);
                }
                *reinterpret_cast<float2*>(smem + OFF_RED + lane * 8) =
                    make_float2((__uint_as_float(g[0].x) + __uint_as_float(g[1].x)) + (__uint_as_float(g[2].x) + __uint_as_float(g[3].x)),
                                (__uint_as_float(g[0].y) + __uint_as_float(g[1].y)) + (__uint_as_float(g[2].y) + __uint_as_float(g[3].y)));
                __syncwarp();
                if (lane == 0) { mbar_arrive(BAR(B_GU)); TRACE(223); }
            }
#pragma unroll 1
            for (int k = 0; k < 3; k++) {
                AT_STEP(k == 0 ? WS1 : k == 1 ? WS2 : WS3);
                WATCH(grp ^ (k >> 1), k >> 1, k ? 0xffffffffu : 0xffffffu);
            }
          } else {
           if (warp == 13) {
                uint8_t* dst = smem + OFF_MO;
                mbar_wait(BAR(B_RSD), 0);
                if (lane < 12) st_relaxed64(&P.scr->rs[part * D_ + eb * 256 + j * 16 + lane], reinterpret_cast<const uint32_t*>(smem + OFF_H)[lane], ep);
                wait_until(t_in + RSD);
                if (lane == 0) TRACE(225);
                uint4 f[4];
                bool ok;
#pragma unroll
                for (int i = 0; i < 4; i++) f[i].y = ~ep;
                do {
                    ok = true;
#pragma unroll
                    for (int i = 0; i < 4; i++)
                        if (f[i].y != ep || f[i].w != ep)
                            f[i] = ld_relaxed128(reinterpret_cast<const uint4*>(P.scr->rs) + part * 512 + eb * 128 + 64 * ((i >> 1) ^ part) + (i & 1) * 32 + lane);
#pragma unroll
                    for (int i = 0; i < 4; i++) ok = ok && f[i].y == ep && f[i].w == ep;
                } while (!__all_sync(0xffffffffu, ok) && IN_TIME());
                if (lane == 0) TRACE(226);
#pragma unroll
                for (int i = 0; i < 8; i++) {
                    const float v = 0.5f * __uint_as_float((i & 1) ? f[i >> 1].z : f[i >> 1].x);
                    const float hi = rbf(v), mid = rbf(v - hi), lo = v - hi - mid;
                    *reinterpret_cast<uint4*>(dst + (((i >> 1) * 32 + lane) * 2 + (i & 1)) * 16) = make_uint4(pack_bf(hi, mid), pack_bf(lo, 0.f), 0, 0);
                }
                fence_async_smem();
                __syncwarp();
                if (lane == 0) { mbar_arrive(BAR(B_STATS)); TRACE(204); }
            }
#define FLAG(w) st_release8(reinterpret_cast<uint8_t*>(&P.scr->abflag[grp * 16 + 2 * (w) + c]) + (j >> 1), ep & 0xffu)
            const int hf = (warp >> 1) & 1;
            if (!hf && elect_one()) {
                mbar_wait(BAR(B_EPI), 0);
                mbar_arrive(BAR(B_HS));
                TRACE(206);
                FLAG(0);
                TRACE(207);
            }
            __syncwarp();
            uint8_t* dst = P.scr->ab + (size_t)(grp * 32 + 2 * j + 1) * B_BYTES + hf * 16384 + lane * 16;
            uint32_t src = sb + OFF_SP + hf * 16384 + lane * 16;
            mbar_wait_sleep(BAR(B_EPI + 3), 0);
            unsigned t0 = clk() + (c ? DELAY2 : DELAY0);
#pragma unroll 1
            for (int i = 0; i < 8; i++, src += 2048, dst += 2048, t0 += SPACE0) {
                wait_until(t0);
                uint4 v[4];
#pragma unroll
                for (int u = 0; u < 4; u++) v[u] = lds128(src + u * 512);
#pragma unroll
                for (int u = 0; u < 4; u++) stg128(dst + u * 512, v[u].x, v[u].y, v[u].z, v[u].w);
            }
            named_bar<3, 64>();
            if (!hf && elect_one()) {
                mbar_arrive(BAR(B_SPF));
                TRACE(209);
                FLAG(1);
                TRACE(210);
            }
          }
        }
    } else if (warp >= 8) {
        asm volatile("setmaxnreg.dec.sync.aligned.u32 %0;" ::"n"(HELP_REGS));
        const int aw = warp - 8, mt = tid - 256;
        float* hact = reinterpret_cast<float*>(smem + OFF_H);
        uint4 buf[NB];
#define WP0() reinterpret_cast<const char*>(((aw & 1) ? P.wu : P.wg) + (size_t)(c * (OWN / 2) + (aw >> 1) * (OWN / 4) + ((tid_now() >> 3) & 3)) * F_ + ci * 64 + (tid_now() & 7) * 8)
        {
            const unsigned t_in = t_first;
            const unsigned ep = load_epoch(&P.scr->epoch[b]);
            uint4 w[4];
            w[0] = __ldg(reinterpret_cast<const uint4*>(P.wr + eb * 256 + lane * 8));
            float s1[4], s2[4], sx[4];
#pragma unroll
            for (int r = 0; r < 4; r++) { s1[r] = 0.f; s2[r] = 0.f; sx[r] = 0.f; }
            const int xr0 = part * 64 + aw * 16 + (lane >> 3);
            const uint32_t xa0 = sb + xr0 * 128 + (((lane & 7) ^ (lane >> 3)) << 4);
            if (sh) { mbar_wait_sleep(BAR(B_FULL), 0); if (lane < 3) mbar_arrive(BAR(B_HRD)); }
#pragma unroll 1
            for (int s = sh; s < sh + 4; s++) {
                const int from = ((s - sh) ^ sh) * 8 + (lane & 7);
                const uint4 wn = make_uint4(__shfl_sync(0xffffffffu, w[0].x, from), __shfl_sync(0xffffffffu, w[0].y, from),
                                            __shfl_sync(0xffffffffu, w[0].z, from), __shfl_sync(0xffffffffu, w[0].w, from));
                const float wf[8] = {bf_lo(wn.x), bf_hi(wn.x), bf_lo(wn.y), bf_hi(wn.y), bf_lo(wn.z), bf_hi(wn.z), bf_lo(wn.w), bf_hi(wn.w)};
                mbar_wait_sleep(BAR(B_FULL + (s & 3)), s >> 2);
                const uint32_t xa = xa0 + (s & 3) * STAGE_BYTES;
                uint4 v[4];
#pragma unroll
                for (int r = 0; r < 4; r++) v[r] = lds128((xa ^ ((r & 1) << 6)) + r * 512);
                if (lane < (((s - sh) >> 1) == part ? 1 : 3)) mbar_arrive_after(BAR(B_HRD + s), v[0].x | v[1].x | v[2].x | v[3].x);
#pragma unroll
                for (int r = 0; r < 4; r++) {
                    const uint32_t xv[4] = {v[r].x, v[r].y, v[r].z, v[r].w};
#pragma unroll
                    for (int e = 0; e < 4; e++) {
                        const float a0 = bf_lo(xv[e]), a1 = bf_hi(xv[e]);
                        s1[r] += a0; s1[r] += a1;
                        s2[r] = fmaf(a1, a1, fmaf(a0, a0, s2[r]));
                        sx[r] = fmaf(a1, wf[2 * e + 1], fmaf(a0, wf[2 * e], sx[r]));
                    }
                    GAP("+f"(s1[r]), "+f"(s2[r]), "+f"(sx[r]));
                }
            }
            if (mt == 0) TRACE(211);
#pragma unroll
            for (int i = 1; i < 4; i++) w[i] = __ldg(reinterpret_cast<const uint4*>(P.wr + (eb ^ i) * 256 + lane * 8));
#define FOLD4(a, H, L) do { const bool uh = lane & (H), ul = lane & (L); \
                float p0 = (uh ? a[2] : a[0]) + __shfl_xor_sync(0xffffffffu, uh ? a[0] : a[2], H); \
                float p1 = (uh ? a[3] : a[1]) + __shfl_xor_sync(0xffffffffu, uh ? a[1] : a[3], H); \
                a[0] = (ul ? p1 : p0) + __shfl_xor_sync(0xffffffffu, ul ? p0 : p1, L); \
                _Pragma("unroll") for (int o = (L) >> 1; o; o >>= 1) a[0] += __shfl_xor_sync(0xffffffffu, a[0], o); } while (0)
            FOLD4(s1, 4, 2); FOLD4(s2, 4, 2); FOLD4(sx, 4, 2);
            if (!(lane & 1))
                st_relaxed128(&P.scr->xp[eb * S_ + j * 128 + xr0 + ((lane & 6) << 1)],
                              make_uint4(__float_as_uint(s1[0]), __float_as_uint(fmaf(s1[0] * (-1.0f / 256), s1[0], s2[0])), __float_as_uint(sx[0]), ep));
            wait_until(clk() + XPD);
            wait_until(t_in + XPT);
            {
                uint4 f[4];
                const uint4* xp = &P.scr->xp[j * 128 + mt];
                bool ok;
#pragma unroll
                for (int i = 0; i < 4; i++) f[i] = ld_relaxed128(xp + i * S_);
                float sw = sum8(w[0]) + sum8(w[1]), sw2;
                GAP("+f"(sw));
                sw2 = sum8(w[2]) + sum8(w[3]);
                GAP("+f"(sw2));
                sw = warp_sum(sw + sw2);
                do {
#pragma unroll
                    for (int i = 0; i < 4; i++) if (f[i].w != ep) f[i] = ld_relaxed128(xp + i * S_);
                    ok = f[0].w == ep && f[1].w == ep && f[2].w == ep && f[3].w == ep;
                } while (!__all_sync(0xffffffffu, ok) && IN_TIME());
                if (mt == 0) TRACE(224);
                const float mean = ((__uint_as_float(f[0].x) + __uint_as_float(f[1].x)) + (__uint_as_float(f[2].x) + __uint_as_float(f[3].x))) * (1.0f / D_);
                float m2 = 0.f, px = 0.f;
#pragma unroll
                for (int i = 0; i < 4; i++) {
                    const float d = fmaf(__uint_as_float(f[i].x), 1.0f / 256, -mean);
                    m2 += fmaf(d * 256.f, d, __uint_as_float(f[i].y));
                    px += __uint_as_float(f[i].z);
                }
                const float mb = rbf(mean);
                float sd, rinv;
                asm("sqrt.approx.ftz.f32 %0, %1;" : "=f"(sd) : "f"(rbf(rbf(fmaxf(m2 * (1.0f / D_), 0.f)) + 1e-5f)));
                asm("rcp.approx.ftz.f32 %0, %1;" : "=f"(rinv) : "f"(rbf(sd)));
                unsigned u = pack_bf(fmaf(-mb, sw, px) * rinv, 0.f);
                u = (u & 0x8000u) ? (~u & 0xffffu) : (u | 0x8000u);
                u = (u << 16) | (0xffffu - (unsigned)(j * 128 + mt));
                if (u == __reduce_max_sync(0xffffffffu, u))
                    *reinterpret_cast<uint4*>(smem + OFF_RED + aw * 16) = make_uint4(u, __float_as_uint(mb), __float_as_uint(rinv), 0);
                named_bar<4, 128>();
                if (aw == 0) {
                    const uint4 g = *reinterpret_cast<const uint4*>(smem + OFF_RED + (lane & 3) * 16);
                    if (g.x == __reduce_max_sync(0xffffffffu, g.x) && lane < 8) st_relaxed128(&P.scr->best[2 * b + (lane >> 2)], make_uint4(g.x, g.y, g.z, ep));
                }
                if (mt == 0) TRACE(212);
                *reinterpret_cast<float2*>(smem + OFF_MO + 4096 + mt * 8) = make_float2(mb, rinv);
                sts128(sb + OFF_MO + 5120 + mt * 16, pack_bf(-mb, -mb), pack_bf(-mb, 0.f), 0, 0);
                fence_async_smem();
                __syncwarp();
                if (lane == 0) mbar_arrive(BAR(B_STATS));
            }
            if (aw == 0) {
                uint4 f;
                wait_until(t_in + BPT);
                do { f = ld_relaxed128(&P.scr->best[2 * (grp * 16 + (lane & 15))]); } while (!__all_sync(0xffffffffu, f.w == ep) && IN_TIME());
                const unsigned key = __reduce_max_sync(0xffffffffu, f.x);
                if (lane < 16 && f.x == key) { *reinterpret_cast<uint4*>(smem + OFF_SEL) = f; mbar_arrive(BAR(B_SEL)); TRACE(200); }
                __syncwarp();
            }
        }
        if (moe) {
            const uint64_t pol = policy_evict_first();
            mbar_wait(BAR(B_SEL), 0);
            {
                const uint4 sl = lds128(sb + OFF_SEL);
                const float m = __uint_as_float(sl.y), ri = __uint_as_float(sl.z);
                const uint2 xv = __ldg(reinterpret_cast<const uint2*>(P.x + (size_t)(0xffff - (int)(sl.x & 0xffffu)) * D_ + c * (OWN / 2) + mt * 4));
                const char* w0 = WP0();
#pragma unroll
                for (int q = 0; q < NB; q++) buf[q] = ldg_stream(w0 + q * 8 * F_, pol);
                const uint32_t n0 = norm2(xv.x, m, ri), n1 = norm2(xv.y, m, ri);
                float* xn = reinterpret_cast<float*>(smem + OFF_XN) + mt;
                xn[0] = bf_lo(n0); xn[132] = bf_hi(n0); xn[264] = bf_lo(n1); xn[396] = bf_hi(n1);
            }
            named_bar<4, 128>();
            float ag[8];
#pragma unroll
            for (int i = 0; i < 8; i++) ag[i] = 0.f;
            uint32_t xq = sb + OFF_XN + (lane >> 3) * 528 + (aw >> 1) * (OWN / 4);
            uint32_t str = 8 * F_;
            const char* wp = WP0() + NB * 8 * F_;
            if (mt == 0) TRACE(213);
            mbar_wait_sleep(BAR(B_EPI + 3), 0);
            wait_until(clk() + GOD);
#pragma unroll 1
            for (int r = 0; r < GR + 4; r++, xq += 32) {
                if (r == GR - 1) { wp = reinterpret_cast<const char*>(P.wd + (size_t)(ci * 64 + c * 32) * D_ + (tid_now() - 256) * 8); str = 2 * D_; }
                if (r == GR + 3) str = 0;
#pragma unroll
                for (int h = 0; h < NB; h += 4) {
                    const uint4 m4 = lds128(xq + h * 4);
                    const uint32_t mv[4] = {m4.x, m4.y, m4.z, m4.w};
#pragma unroll
                    for (int q = 0; q < 4; q++) {
                        fma8(ag, buf[h + q], __uint_as_float(mv[q]));
                        GAP(R8(ag, 0));
                        ldg_stream_next(buf[h + q], wp, str, pol);
                    }
                }
                if (r != GR - 1) continue;
                const int lane = tid_now() & 31;
            {
                const bool uh = lane & 16, ul = lane & 8;
#pragma unroll
                for (int i = 0; i < 4; i++) ag[i] = (uh ? ag[i + 4] : ag[i]) + __shfl_xor_sync(0xffffffffu, uh ? ag[i] : ag[i + 4], 16);
#pragma unroll
                for (int i = 0; i < 2; i++) ag[i] = (ul ? ag[i + 2] : ag[i]) + __shfl_xor_sync(0xffffffffu, ul ? ag[i] : ag[i + 2], 8);
            }
            named_bar<4, 128>();
            float* ps = reinterpret_cast<float*>(smem + OFF_XN);
            *reinterpret_cast<float2*>(&ps[aw * 64 + (lane & 7) * 8 + (lane >> 3) * 2]) = make_float2(ag[0], ag[1]);
            named_bar<4, 128>();
            if (aw == 0) {
                const int o = (c ^ 1) * 32 + lane, m = c * 32 + lane;
                if (lane == 0) { mbar_expect_tx(BAR(B_PEER), 256); mbar_expect_tx(BAR(B_PR2), 2048); }
                const float go = ps[m] + ps[128 + m], uo = ps[64 + m] + ps[192 + m], gx = ps[o] + ps[128 + o], ux = ps[64 + o] + ps[192 + o];
                __syncwarp();
                st_async2(mapa(sb + OFF_RED + 256 + lane * 8, c ^ 1), gx, ux, mapa(BAR(B_PEER), c ^ 1));
                mbar_wait(BAR(B_GU), 0);
                mbar_wait_cluster(BAR(B_PEER), 0);
                const float2 pv = *reinterpret_cast<const float2*>(smem + OFF_RED + 256 + lane * 8);
                const float2 pq = *reinterpret_cast<const float2*>(smem + OFF_RED + lane * 8);
                hact[lane] = rbf(rbf(silu_f(rbf((go + pv.x) + pq.x))) * rbf((uo + pv.y) + pq.y));
                if (lane == 0) TRACE(214);
            }
            named_bar<4, 128>();
#pragma unroll
            for (int i = 0; i < 8; i++) ag[i] = 0.f;
            xq = sb + OFF_H - 32;
            }
            const int mt = tid_now() - 256;
            const unsigned ep = lds128(sb + OFF_SEL).w;
            if ((aw >> 1) != c) {
                const uint32_t rem = mapa(sb + OFF_XN + (mt & 63) * 16, c ^ 1);
                st_async4(rem, ag[0], ag[1], ag[2], ag[3], mapa(BAR(B_PR2), c ^ 1));
                st_async4(rem + 1024, ag[4], ag[5], ag[6], ag[7], mapa(BAR(B_PR2), c ^ 1));
                uint4* clr = &P.scr->part[(((ep + 1) & 1) * (NMOE / 2) + ci) * (D_ / 4) + mt];
                st_relaxed128(clr, make_uint4(0, 0, 0, 0));
                st_relaxed128(clr + 128, make_uint4(0, 0, 0, 0));
            } else {
                mbar_wait_cluster(BAR(B_PR2), 0);
                const float4 p0 = *reinterpret_cast<const float4*>(smem + OFF_XN + (mt & 63) * 16);
                const float4 p1 = *reinterpret_cast<const float4*>(smem + OFF_XN + 1024 + (mt & 63) * 16);
                uint4* dst = &P.scr->part[((ep & 1) * (NMOE / 2) + ci) * (D_ / 4) + mt];
                st_relaxed128(dst, make_uint4(~__float_as_uint(ag[0] + p0.x), __float_as_uint(ag[1] + p0.y), __float_as_uint(ag[2] + p0.z), __float_as_uint(ag[3] + p0.w)));
                st_relaxed128(dst + 128, make_uint4(~__float_as_uint(ag[4] + p1.x), __float_as_uint(ag[5] + p1.y), __float_as_uint(ag[6] + p1.z), __float_as_uint(ag[7] + p1.w)));
            }
            if (mt == 0) TRACE(215);
        }
        mbar_wait_sleep(BAR(B_SEL), 0);
        const uint4 sl = lds128(sb + OFF_SEL);
        const unsigned key = sl.x, ep = sl.w;
        const int sel = 0xffff - (int)(key & 0xffffu);
        const float2 st = make_float2(__uint_as_float(sl.y), __uint_as_float(sl.z));
        if ((sel >> 8) == (j >> 1)) {
            const int lane = tid_now() & 31;
            const uint4* src = &P.scr->part[((ep & 1) * (NMOE / 2) + (c * 4 + aw) * 7) * (D_ / 4) + (lane & 1) * 128 + eb * 32 + part * 16 + (lane >> 1)];
            float4* park = reinterpret_cast<float4*>(smem + OFF_PARK) + lane;
            const uint2 xv = __ldg(reinterpret_cast<const uint2*>(P.x + (size_t)sel * D_ + eb * 256 + part * 128 + lane * 4));
            AT_STEP(FRS);
            if (mt == 0) TRACE(220);
            uint4 t[7];
#pragma unroll
            for (int u = 0; u < 7; u++) t[u].x = 0;
            bool ok;
            do {
#pragma unroll
                for (int u = 0; u < 7; u++) if (t[u].x == 0) t[u] = ld_relaxed128(src + u * (D_ / 4));
                ok = true;
#pragma unroll
                for (int u = 0; u < 7; u++) ok = ok && t[u].x != 0;
            } while (!__all_sync(0xffffffffu, ok) && IN_TIME());
            float4 a4 = make_float4(0.f, 0.f, 0.f, 0.f);
#pragma unroll
            for (int u = 0; u < 7; u++) {
                a4.x += __uint_as_float(~t[u].x); a4.y += __uint_as_float(t[u].y); a4.z += __uint_as_float(t[u].z); a4.w += __uint_as_float(t[u].w);
            }
            if (mt == 0) TRACE(221);
            mbar_wait(BAR(he_bar(DEADH)), he_par(DEADH));
            park[aw * 32] = a4;
            named_bar<4, 128>();
            if (mt == 0) TRACE(222);
            if (aw == 0) {
#pragma unroll
                for (int w = 1; w < 4; w++) { const float4 q = park[w * 32]; a4.x += q.x; a4.y += q.y; a4.z += q.z; a4.w += q.w; }
            }
            if (aw == 0 && (sel >> 7) != j) {
                st_async4(mapa(sb + OFF_RED + lane * 16, c ^ 1), a4.x, a4.y, a4.z, a4.w, mapa(BAR(B_FIN), c ^ 1));
            } else if (aw == 0) {
                if (lane == 0) mbar_expect_tx(BAR(B_FIN), 512);
                unsigned u = key >> 16;
                u = (u & 0x8000u) ? (u & 0x7fffu) : (~u & 0xffffu);
                const float sg = rbf(__fdividef(1.0f, 1.0f + __expf(-__uint_as_float(u << 16))));
                const uint32_t n0 = norm2(xv.x, st.x, st.y), n1 = norm2(xv.y, st.x, st.y);
                mbar_wait_cluster(BAR(B_FIN), 0);
                const float4 q = *reinterpret_cast<const float4*>(smem + OFF_RED + lane * 16);
                a4.x += q.x; a4.y += q.y; a4.z += q.z; a4.w += q.w;
                uint2 o;
                o.x = silu2(pack_bf(bf_lo(n0) + rbf(rbf(a4.x) * sg), bf_hi(n0) + rbf(rbf(a4.y) * sg)));
                o.y = silu2(pack_bf(bf_lo(n1) + rbf(rbf(a4.z) * sg), bf_hi(n1) + rbf(rbf(a4.w) * sg)));
                if (lane == 0) TRACE(216);
                *reinterpret_cast<uint2*>(smem + OFF_GROW + lane * 8) = o;
                __syncwarp();
                if (lane == 0) mbar_arrive(BAR(B_UPD));
            }
        }
    } else {
        asm volatile("setmaxnreg.inc.sync.aligned.u32 %0;" ::"n"(CONS_REGS));
        const int wg = warp >> 2, wq = warp & 3;
        const int wt = tid & 127;
#define P4OK 0
        const int one = __shfl_sync(0xffffffffu, blockIdx.y + 1, 0);
        TRACE_C(50);
        float acc[128];
        const uint32_t rel_bar = mapa(BAR(B_EMPTY), (uint32_t)(wt >> 5) & 1);
        const bool rel_thr = (wt == 0) || (wt == 32);
#define RELEASE(s) do { if (rel_thr) mbar_arrive_cluster(rel_bar + 8u * (s)); } while (0)
        const uint32_t dA0 = desc_lo(SB0, 16) + wg * 512;
        constexpr uint32_t dBk0 = desc_lo(SB0 + A_BYTES, 16);
        constexpr uint32_t dBn0 = desc_lo(SB0, 4096);
        constexpr uint32_t ST = STAGE_BYTES >> 4;
        const int row_l = wg * 64 + wq * 16 + (lane >> 2);

        const uint32_t ioff = wq * 1024 + (lane >> 2) * 64 + (((lane & 3) ^ (lane >> 3)) << 4);
        uint32_t sdst = sb + (wg ? OFF_SP : OFF_X) + ioff;
        uint8_t* gdst = P.scr->ab + (size_t)(grp * 32 + 2 * j) * B_BYTES + ioff;
        asm volatile("" : "+l"(gdst), "+r"(sdst));

#define MMA1_H(O, s, first) do { _Pragma("unroll") for (int kk = 0; kk < 4; kk++) \
            wgmma128<O, 0>(acc, dA0 + (s) * ST + kk * 2, dBk0 + (s) * ST + kk * 2 + (O) * 16, !((first) && kk == 0)); } while (0)
#define WAIT_FULL(s, ph, it) do { mbar_wait(BAR(B_FULL + (s)), ph); TRACE_C(it); } while (0)
#define MMA1(s, first, rel) do { wg_fence(); MMA1_H(0, s, first); wg_commit(); wg_wait<1>(); rel; \
            wg_fence(); MMA1_H(64, s, first); wg_commit(); } while (0)
#define PROF5 0
#define WAIT_FULL_L(s, ph, it) WAIT_FULL(s, ph, it)
#define STEP1(s, ph, it, first, rel) do { WAIT_FULL_L(s, ph, it); MMA1(s, first, rel); } while (0)
        uint32_t xr[32];
        const uint32_t xad = sb + row_l * 128 + ((((lane & 4) + (lane & 3)) ^ (lane >> 2)) << 4);
#define XLOAD(s) do { if ((unsigned)(4 * o + (s) - sh - 2 * part) < 2u) { _Pragma("unroll") for (int h = 0; h < 4; h++) { \
            const uint4 u = lds128((xad ^ ((h >> 1) << 6)) + (s) * STAGE_BYTES + (h & 1) * 1024); \
            uint32_t* e = xr + 16 * ((s) & 1) + 4 * h; e[0] = u.x; e[1] = u.y; e[2] = u.z; e[3] = u.w; } \
            } } while (0)
#define XDONE(s) do { if ((unsigned)(4 * o + (s) - sh - 2 * part) < 2u && lane == 0) { const uint32_t* e = xr + 16 * ((s) & 1); \
            mbar_arrive_after(BAR(B_HRD + 4 * o + (s)), e[0] | e[4] | e[8] | e[12]); } } while (0)
#pragma unroll
        for (int i = 0; i < 32; i++) xr[i] = 0;
        TRACE_C(51);
#pragma unroll 1
        for (int o = 0; o < 3; o++) {
            STEP1(0, o & 1, 4 * o, o == 0, if (o) RELEASE(3); XDONE(-1)); XLOAD(0);
            STEP1(1, o & 1, 4 * o + 1, false, RELEASE(0); XDONE(0)); XLOAD(1);
            STEP1(2, o & 1, 4 * o + 2, false, RELEASE(1); XDONE(1)); XLOAD(2);
            STEP1(3, o & 1, 4 * o + 3, false, RELEASE(2); XDONE(2)); XLOAD(3);
        }
#define XSWAP() do { const bool odd = lane & 4; _Pragma("unroll") for (int i = 0; i < 24; i++) if (!(i & 8)) { \
            const uint32_t u0 = xr[i], u1 = xr[i + 8]; xr[i] = odd ? u1 : u0; xr[i + 8] = odd ? u0 : u1; } } while (0)
        XSWAP();
#define MEAN(O) wgmma128_k8<O>(acc, ((SB0 + OFF_MO + 5120) >> 4) + wg * 64, ((SB0 + OFF_MO) >> 4) + 2 * (O))
#define ROWSTAT() do { mbar_wait(BAR(B_STATS), 0); \
            st0 = *reinterpret_cast<const float2*>(smem + OFF_MO + 4096 + row_l * 8); \
            st1 = *reinterpret_cast<const float2*>(smem + OFF_MO + 4096 + row_l * 8 + 64); \
            rs0 = part ? -st0.y : st0.y; rs1 = part ? -st1.y : st1.y; } while (0)
#define PACK1(p, O, i) do { const float rs_ = ((i) & 1) ? rs1 : rs0; _Pragma("unroll") for (int e = 0; e < 4; e++) { \
                const int k = (O) + 16 * ((i) >> 1) + 4 * e + 2 * ((i) & 1); p[4 * (i) + e] = pack_bf(acc[k] * rs_, acc[k + 1] * rs_); } } while (0)
#define IOFF(O, i) ((O) * 256 + ((i) >> 1) * 4096 + ((i) & 1) * 512)
#define STS1(p, O, i) sts128(sdst + IOFF(O, i), p[4 * (i)], p[4 * (i) + 1], p[4 * (i) + 2], p[4 * (i) + 3])
#define STG1(p, O, i) stg128(gdst + IOFF(O, i), p[4 * (i)], p[4 * (i) + 1], p[4 * (i) + 2], p[4 * (i) + 3])
#define PIECES(p, O, G) PIECES_(p, O, G, 0, 8)
#define PIECES_(p, O, G, i0, i1) do { _Pragma("unroll") for (int i = (i0); i < (i1); i += 2) { PACK1(p, O, i); PACK1(p, O, i + 1); \
                ONCE(if (G) { STG1(p, O, i); STG1(p, O, i + 1); } else { STS1(p, O, i); STS1(p, O, i + 1); }); } } while (0)
#define BURST(ST, sp) do { unsigned tb = clk(); _Pragma("unroll") for (int i = 0; i < 16; i += 2) { \
                if (i < 8) { ST(pl, 0, i); ST(pl, 0, i + 1); } else { ST(pr, 64, i - 8); ST(pr, 64, i - 7); } \
                if (sp && i < 14) { tb += sp; while ((int)(clk() - tb) < 0) {} } } } while (0)
#define STAGED(i) do { fence_async_smem(); __syncwarp(); if (lane == 0) mbar_arrive(BAR(B_EPI + (i))); } while (0)
        float ac2[128];
#define MMA_F(O, aoff, boff, first) do { wg_fence(); _Pragma("unroll") for (int kk = 0; kk < 4; kk++) \
            wgmma128<O>(ac2, dA0 + ((aoff) >> 4) + kk * 2, dBn0 + ((boff) >> 4) + kk * 64, !((first) && kk == 0)); wg_commit(); } while (0)
#define LEFT16() do { mbar_wait(BAR(B_EPI + 1), 0); WAIT_FULL(0, 0, 16); MMA_F(0, 0, OFF_X, true); } while (0)
#define STAMP(k) do {} while (0)
        float2 st0, st1;
        float rs0, rs1;
        uint32_t pl[32], pr[32];
        if (wg == 0) {
            STEP1(0, 1, 12, false, RELEASE(3));
            STEP1(1, 1, 13, false, RELEASE(0));
            STEP1(2, 1, 14, false, RELEASE(1));
            STAMP(0);
            ROWSTAT();
            STAMP(1);
            wg_fence(); MEAN(64); MEAN(0);
            WAIT_FULL(3, 1, 15);
            STAMP(2);
            wg_fence(); MMA1_H(0, 3, false); wg_commit();
            MMA1_H(64, 3, false); wg_commit();
            named_arrive<5, 256>();
            const bool pub = c == 0;
            wg_wait<1>();
            fence_regs64<0>(acc);
            TRACE_C(52);
            STAMP(3);
            PIECES(pl, 0, pub);
            TRACE_C(53);
            STAMP(4);
            wg_wait<0>();
            fence_regs64<64>(acc);
            STAMP(5);
            RELEASE(2); RELEASE(3);
            if (tid == 0) mbar_arrive(BAR(B_W0D));
            mbar_wait(BAR(B_W1M), 0);
            TRACE_C(54);
            PIECES(pr, 64, pub);
            STAMP(6);
            if (pub) {
                __syncwarp();
                if (lane == 0) mbar_arrive(BAR(B_EPI + 0));
                mbar_wait(BAR(B_HS), 0);
                STAMP(7);
                BURST(STS1, BSP0);
            }
            STAGED(1);
            STAMP(8);
            if (!pub) {
                BURST(STG1, BSP1);
                __syncwarp();
                if (lane == 0) mbar_arrive(BAR(B_EPI + 0));
            }
            STAMP(9);
            LEFT16();
            STAMP(10);
        } else {
            wg_wait<0>(); RELEASE(3);
            ROWSTAT();
            wg_fence(); MEAN(64); MEAN(0); wg_commit();
            wg_wait<0>();
            if (lane == 0) mbar_arrive(BAR(B_W1M));
            named_bar<5, 256>();
            TRACE_C(12);
            STAMP(0);
            wg_fence(); MMA1_H(0, 0, false); MMA1_H(64, 0, false); wg_commit();
            MMA1(1, false, STAMP(1); RELEASE(0));
            wg_fence(); MMA1_H(0, 2, false); wg_commit();
            wg_wait<1>(); STAMP(2); RELEASE(1);
            mbar_wait(BAR(B_W0D), 0);
            wg_fence(); MMA1_H(0, 3, false); wg_commit();
            MMA1_H(64, 2, false); MMA1_H(64, 3, false); wg_commit();
            STAMP(3);
            wg_wait<1>();
            fence_regs64<0>(acc);
            TRACE_C(52);
            STAMP(4);
            PIECES_(pl, 0, false, 0, 4);
            STAMP(5);
            wg_wait<0>();
            fence_regs64<64>(acc);
            STAMP(6);
            RELEASE(2); RELEASE(3);
            PIECES_(pl, 0, false, 4, 8);
            TRACE_C(53);
            STAGED(2);
            STAMP(7);
            LEFT16();
            STAMP(8);
            TRACE_C(54);
            PIECES(pr, 64, false);
            STAGED(3);
            STAMP(9);
        }
        TRACE_C(55);

#define MMA2K(aoff, boff, k0) do { wg_fence(); _Pragma("unroll") \
        for (int kk = k0; kk < k0 + 2; kk++) { \
            wgmma128<0>(ac2, dA0 + ((aoff) >> 4) + kk * 2, dBn0 + ((boff) >> 4) + kk * 64, 1); \
            wgmma128<64>(ac2, dA0 + ((aoff) >> 4) + kk * 2, dBn0 + ((boff) >> 4) + kk * 64 + 1024, 1); } } while (0)
#define STEP2(s, ph, it) do { WAIT_FULL_L(s, ph, it); if (PROF5 && (it) < 34) STAMP(15 + (it) - 18); MMA2K((s) * STAGE_BYTES, b2_off(s), 0); \
            wg_commit(); wg_wait<1>(); RELEASE(((s) + 3) & 3); \
            MMA2K((s) * STAGE_BYTES, b2_off(s), 2); wg_commit(); } while (0)
#define MMA_H(O, aoff, boff) MMA_F(O, aoff, boff, false)
        MMA_F(64, 0, OFF_X + 16384, true);
        STAMP(11);
        mbar_wait(BAR(B_EPI + 2), 0); mbar_wait(BAR(B_FULL + 1), 0);
        STAMP(12);
        MMA_H(0, STAGE_BYTES, OFF_SP);
        wg_wait<1>(); STAMP(13); RELEASE(0);
        mbar_wait(BAR(B_EPI + 3), 0);
        STAMP(14);
        TRACE_C(17);
        MMA_H(64, STAGE_BYTES, OFF_SP + 16384);
        uint32_t g[32];
        const float mr0 = -st0.x * st0.y, mr1 = -st1.x * st1.y;
#define GATE(i) do { _Pragma("unroll") for (int e = (i); e < (i) + 4; e++) { \
                g[16 + e] = gate2(o == GATE_O ? xr[e] : xr[16 + e], ((i) & 4) ? st1.y : st0.y, ((i) & 4) ? mr1 : mr0); \
                g[e] = o == GATE_O ? g[16 + e] : g[e]; } } while (0)
#pragma unroll
        for (int i = 0; i < 32; i++) g[i] = 0;
#pragma unroll 1
        for (int o = 4;; o++) {
            const bool gt = (unsigned)(o - GATE_O) < 2u;
            STEP2(2, o & 1, 4 * o + 2);
            if (RS == 4 && o == 10) break;
            if (o == 4 && wt == 0) mbar_arrive(BAR(B_SPF));
            if (gt) GATE(0);
            STEP2(3, o & 1, 4 * o + 3);
            if (RS == 7 && o == 9) break;
            if (gt) GATE(4);
            STEP2(0, ~o & 1, 4 * o + 4);
            if (RS == 6 && o == 9) break;
            if (gt) GATE(8);
            STEP2(1, ~o & 1, 4 * o + 5);
            if (RS == 5 && o == 9) break;
            if (gt) GATE(12);
        }
#undef P4OK
#define P4OK 1
#define HSTEP(h) MMA_H(0, ha_off(h), hb_off(h))
        mbar_wait(BAR(B_SEL), 0);
        const uint32_t tag = __shfl_sync(0xffffffffu, *reinterpret_cast<volatile unsigned*>(smem + OFF_SEL + 12) & 1, 0);
        uint4* xdst = P.scr->xch + (size_t)(b ^ 16) * 2048 + tid_now();
        asm volatile("" : "+l"(xdst));
        __uint128_t sv[8];
#define SENT(tab, p) ((p) > 12 ? 8 : (int)((((unsigned long long)(tab) | 0x888888888888ull << (4 * SNDN)) << 4 >> (4 * (p))) & 15))
#define SEND(p) do { _Pragma("unroll") for (int v = 0; v < 8; v++) { \
            const bool s0 = v >= SENT(SND0, p) && v < SENT(SND0, (p) + 1), s1 = v >= SENT(SND1, p) && v < SENT(SND1, (p) + 1); \
            if (wg ? s1 : s0) st_relaxed128(xdst + v * 256, sv[v]); } } while (0)
        WAIT_FULL(hs(3), hp(3) ^ 1, 47 - RS);
        MMA_H(64, hs(3) * STAGE_BYTES, b2_off(hs(3)) + 16384);
        wg_wait<1>(); RELEASE(hs(2));
        MMA_H(0, hs(3) * STAGE_BYTES, b2_off(hs(3)));
        mbar_wait(BAR(hf_bar(0)), hf_par(0));
        HSTEP(0);
        wg_wait<2>();
        fence_regs64<64>(ac2);
        TRACE_C(56);
#pragma unroll
        for (int v = 0; v < 8; v++) {
            const int k = 64 + 16 * (v >> 1) + 2 * (v & 1);
            sv[v] = make128((pack_bf(ac2[k], ac2[k + 1]) & ~1u) | tag, pack_bf(ac2[k + 4], ac2[k + 5]), pack_bf(ac2[k + 8], ac2[k + 9]), pack_bf(ac2[k + 12], ac2[k + 13]));
        }
        SEND(0);
        wg_wait<1>(); RELEASE(hs(3));
        uint4 rv[8];
        const uint4* const xsrc = xdst + (part ? 16 * 2048 : -16 * 2048);
        unsigned probe = tag;
#define FETCH_RV() do { _Pragma("unroll") for (int v = 0; v < 8; v++) rv[v] = ld_relaxed128(xsrc + v * 256); } while (0)
#define PROBE() probe = ld_relaxed(&xsrc[7 * 256 + 31 - (tid_now() & 31)].x)
#define AFTER(h) do { \
            if (PRB == PRB1 ? NH - PRB == (h) : NH - PRB == (h) ? wg == 0 : NH - PRB1 == (h) && wg == 1) PROBE(); \
            if (RCV == RCV1 ? NH - RCV == (h) : NH - RCV == (h) ? wg == 0 : NH - RCV1 == (h) && wg == 1) ONCE(if (!((probe ^ tag) & 1)) FETCH_RV();); \
            if (STG && NH - 9 + STG == (h) && wg == 1) { \
                if (POLL1 && ((probe ^ tag) & 1)) {        \
                    _Pragma("unroll 1") for (int k = 0; k < POLL1; k++) { PROBE(); if (!((probe ^ tag) & 1)) { FETCH_RV(); break; } } } \
                named_bar<8, 256>(); } } while (0)
#define HALF(h) do { mbar_wait(BAR(hf_bar(h)), hf_par(h)); TRACE_C((h) + 7 >= NH ? 44 + 7 + (h) - NH : 63); HSTEP(h); SEND(h); \
            if ((h) + 6 < NH || (h) - 1 == DEADH) { wg_wait<1>(); RELEASE(he_bar((h) - 1) - B_EMPTY); } } while (0)
#define HALF_A(h) do { if ((h) < NH && (h) <= SNDN) HALF(h); } while (0)
#define HALF_B(h) do { if ((h) < NH && (h) > SNDN) { HALF(h); AFTER(h); } } while (0)
        HALF_A(1); HALF_A(2); HALF_A(3); HALF_A(4); HALF_A(5); HALF_A(6); HALF_A(7); HALF_A(8);
        TRACE_C(57);
#pragma unroll
        for (int v = 0; v < 8; v++) rv[v] = make_uint4(~tag, 0, 0, 0);
        AFTER(SNDN);
        HALF_B(1); HALF_B(2); HALF_B(3); HALF_B(4); HALF_B(5); HALF_B(6); HALF_B(7); HALF_B(8); HALF_B(9); HALF_B(10); HALF_B(11); HALF_B(12); HALF_B(13);
        if (STG && wg == 0) named_arrive<8, 256>();
        TRACE_C(58);
        const int t2 = tid_now();
        __nv_bfloat16* op = P.out + (size_t)(j * 128 + (t2 >> 5) * 16 + ((t2 >> 2) & 7)) * D_ + eb * 256 + part * 128 + (t2 & 3) * 8;
        asm volatile("" : "+l"(op));
        const int sl = 0xffff - (int)(*reinterpret_cast<volatile unsigned*>(smem + OFF_SEL) & 0xffffu) - j * 128 - (t2 >> 5) * 16;
        const bool lo = ((t2 >> 2) & 7) == sl, hi = ((t2 >> 2) & 7) + 8 == sl;
        if ((unsigned)sl < 16u) {
            mbar_wait(BAR(B_UPD), 0);
#pragma unroll
            for (int a = 0; a < 4; a++) {
                const uint4 u = lds128(sb + OFF_GROW + a * 64 + (t2 & 3) * 16);
                if (lo) { g[8 * a] = u.x; g[8 * a + 1] = u.y; g[8 * a + 2] = u.z; g[8 * a + 3] = u.w; }
                if (hi) { g[8 * a + 4] = u.x; g[8 * a + 5] = u.y; g[8 * a + 6] = u.z; g[8 * a + 7] = u.w; }
            }
        }
        while (true) {
            uint32_t bad = 0;
#pragma unroll
            for (int v = 0; v < 8; v++) bad |= rv[v].x ^ tag;
            if (__all_sync(0xffffffffu, !(bad & 1)) || !IN_TIME()) break;
            if ((t2 & 31) == 31) { while (((ld_relaxed(&xsrc[7 * 256].x) ^ tag) & 1) && IN_TIME()) {} }
            __syncwarp();
#pragma unroll
            for (int v = 0; v < 8; v++) rv[v] = ld_relaxed128(xsrc + v * 256);
        }
        TRACE_C(59);
        ONCE(_Pragma("unroll") for (int v = 0; v < 8; v++) {
            const int i = 4 * v;
            xr[i] = bfma2(rv[v].x & ~1u, g[i], xr[i]); xr[i + 1] = bfma2(rv[v].y, g[i + 1], xr[i + 1]);
            xr[i + 2] = bfma2(rv[v].z, g[i + 2], xr[i + 2]); xr[i + 3] = bfma2(rv[v].w, g[i + 3], xr[i + 3]);
        });
        wg_wait<0>();
        fence_regs64<0>(ac2);
        TRACE_C(60);
#pragma unroll
        for (int n = 0; n < 8; n += 2) {
            uint32_t o[8];
#pragma unroll
            for (int e = 0; e < 8; e++) {
                const int h = n >> 2, a = (n & 3) + (e >> 2), k = 16 * a + 2 * h + 4 * (e & 3), i = 8 * a + 4 * h + (e & 3);
                o[e] = bfma2(pack_bf(ac2[k], ac2[k + 1]), g[i], xr[i]);
            }
            ONCE(stg128(op + (n >> 2) * 8 * D_ + (n & 3) * 32, o[0], o[1], o[2], o[3]);
                 stg128(op + (n >> 2) * 8 * D_ + (n & 3) * 32 + 32, o[4], o[5], o[6], o[7]););
        }
    }
}

typedef CUresult (*EncodeFn)(CUtensorMap*, CUtensorMapDataType, cuuint32_t, void*, const cuuint64_t*, const cuuint64_t*,
                             const cuuint32_t*, const cuuint32_t*, CUtensorMapInterleave, CUtensorMapSwizzle,
                             CUtensorMapL2promotion, CUtensorMapFloatOOBfill);

void make_map(EncodeFn fn, CUtensorMap* tm, const void* p, uint64_t rows, uint64_t cols) {
    cuuint64_t dims[2] = {cols, rows};
    cuuint64_t strides[1] = {cols * 2};
    cuuint32_t box[2] = {64, 128};
    cuuint32_t es[2] = {1, 1};
    fn(tm, CU_TENSOR_MAP_DATA_TYPE_BFLOAT16, 2, const_cast<void*>(p), dims, strides, box, es, CU_TENSOR_MAP_INTERLEAVE_NONE,
       CU_TENSOR_MAP_SWIZZLE_128B, CU_TENSOR_MAP_L2_PROMOTION_L2_128B, CU_TENSOR_MAP_FLOAT_OOB_FILL_NONE);
}

}

extern "C" void kernel_launch(void* const* d_in, const int* in_sizes, int n_in, void* d_out, int out_size) {
    (void)in_sizes; (void)n_in; (void)out_size;
    static EncodeFn fn = nullptr;
    static void* scr = nullptr;
    static bool by_sm = false;
    if (!fn) {
        void* p = nullptr;
        cudaDriverEntryPointQueryResult q;
        cudaGetDriverEntryPoint("cuTensorMapEncodeTiled", &p, cudaEnableDefault, &q);
        fn = (EncodeFn)p;
        cudaGetSymbolAddress(&scr, g_scr);
        int dev = 0, sms = 0;
        cudaGetDevice(&dev);
        cudaDeviceGetAttribute(&sms, cudaDevAttrMultiProcessorCount, dev);
        by_sm = sms == NCTA + 4;
        cudaFuncSetAttribute(by_sm ? fnet_fused_kernel<true> : fnet_fused_kernel<false>, cudaFuncAttributeMaxDynamicSharedMemorySize, SMEM_BYTES);
    }
    CUtensorMap tx, tdre, tdim, tcre, tcim;
    make_map(fn, &tx, d_in[0], S_, D_);
    make_map(fn, &tcre, d_in[1], S_, S_);
    make_map(fn, &tcim, d_in[2], S_, S_);
    make_map(fn, &tdre, d_in[3], D_, D_);
    make_map(fn, &tdim, d_in[4], D_, D_);
    Params P;
    P.x = (const __nv_bfloat16*)d_in[0];
    P.dre = (const __nv_bfloat16*)d_in[3];
    P.dim = (const __nv_bfloat16*)d_in[4];
    P.cre = (const __nv_bfloat16*)d_in[1];
    P.cim = (const __nv_bfloat16*)d_in[2];
    P.wr = (const __nv_bfloat16*)d_in[6];
    P.wg = (const __nv_bfloat16*)d_in[7];
    P.wu = (const __nv_bfloat16*)d_in[8];
    P.wd = (const __nv_bfloat16*)d_in[9];
    P.out = (__nv_bfloat16*)d_out;
    P.scr = (Scratch*)scr;
    if (by_sm) fnet_fused_kernel<true><<<NCTA + 4, NTHREADS, SMEM_BYTES, cudaStreamPerThread>>>(tx, tdre, tdim, tcre, tcim, P);
    else fnet_fused_kernel<false><<<NCTA + 4, NTHREADS, SMEM_BYTES, cudaStreamPerThread>>>(tx, tdre, tdim, tcre, tcim, P);
}
```
